```python
import torch

def _softmax(x, axis=-1):
    return torch.softmax(x, dim=axis)
def _gelu(x):
    return torch.nn.functional.gelu(x, approximate="tanh")
def _silu(x):
    return torch.nn.functional.silu(x)
def _sigmoid(x):
    return torch.sigmoid(x)
def _layernorm(x, axis=-1, eps=1e-5):
    m = x.mean(dim=axis, keepdim=True)
    v = x.var(dim=axis, keepdim=True, unbiased=False)
    return (x - m) / torch.sqrt(v + eps)
def _scatter_add(tgt, idx, src, axis=0):
    return tgt.clone().index_add_(axis, idx, src)
def _segment_sum(src, seg, n):
    out = torch.zeros((n,) + src.shape[1:], dtype=src.dtype)
    return out.index_add_(0, seg, src)
def _pad(x, pw):
    flat = tuple(v for pair in reversed(pw) for v in pair)
    return torch.nn.functional.pad(x, flat)

kernel_name = 'standalone__hybrid_graph_tf_exphormer__graph'

def setup_inputs():

    _w = (lambda a: (lambda t: t.to(torch.bfloat16) if t.is_floating_point() else t)(torch.as_tensor(a)))
    N, deg, D = 10000, 16, 256
    E = N * deg
    exp_deg = 4
    Ee = N * exp_deg
    src = (lambda lo, hi, *s: torch.randint(lo, hi, s))(0, N, E).to(torch.int64)
    dst = (lambda lo, hi, *s: torch.randint(lo, hi, s))(0, N, E).to(torch.int64)
    esrc = (lambda lo, hi, *s: torch.randint(lo, hi, s))(0, N, Ee).to(torch.int64)
    edst = torch.repeat_interleave(torch.arange(N), exp_deg).to(torch.int64)
    deg_cnt = torch.bincount(dst, minlength=N).to(float) + 1.0
    return {
        "x": _w((lambda *s: torch.randn(*s, dtype=torch.bfloat16) * 0.05)(N, D)),
        "src": _w(src),
        "dst": _w(dst),
        "esrc": _w(esrc),
        "edst": _w(edst),
        "deg_inv_sqrt": _w(1.0 / (lambda _x: torch.sqrt(torch.as_tensor(_x)))(deg_cnt)),
        "w_l": _w((lambda *s: torch.randn(*s, dtype=torch.bfloat16) * 0.05)(D, D)),
        "wq": _w((lambda *s: torch.randn(*s, dtype=torch.bfloat16) * 0.05)(D, D)),
        "wk": _w((lambda *s: torch.randn(*s, dtype=torch.bfloat16) * 0.05)(D, D)),
        "wv": _w((lambda *s: torch.randn(*s, dtype=torch.bfloat16) * 0.05)(D, D)),
    }

def reference(x, src, dst, esrc, edst, deg_inv_sqrt, w_l, wq, wk, wv):
    N, D = x.shape
    h = x @ w_l
    msg = h[src] * deg_inv_sqrt[src, None] * deg_inv_sqrt[dst, None]
    h_local = _segment_sum(msg, dst, N)
    q = x @ wq
    k = x @ wk
    v = x @ wv
    e = (q[edst] * k[esrc]).sum(-1) * (D ** -0.5)
    exp_e = torch.exp(e)
    denom = _segment_sum(exp_e[:, None], edst, N)[:, 0] + 1e-9
    alpha = exp_e / denom[edst]
    h_attn = _segment_sum(alpha[:, None] * v[esrc], edst, N)
    return h_local + h_attn
```

```cpp
#include <cuda_runtime.h>
#include <cuda_bf16.h>
#include <cuda.h>
#include <stdint.h>

#define PROFILE 0

namespace gk {

constexpr int N      = 10000;
constexpr int D      = 256;
constexpr int NPC    = 80;
constexpr int NCTA   = 128;
constexpr int RCTA   = N / NPC;
constexpr int NSET   = N / 8;
constexpr int GW     = 16;
constexpr int LW     = 8;
constexpr int AW     = GW + LW;
constexpr int GT     = GW * 32, LT = LW * 32;
constexpr int NTHR   = (AW + 4) * 32;
constexpr int UPQ    = 156;
constexpr int OVCAP  = 64;
constexpr int SPIN_LIMIT = 1 << 20;

constexpr int KB      = NPC * 128;
constexpr int UNIT    = 8192;
constexpr int SM_S    = 0;
constexpr int SM_X    = 20 * UNIT;
constexpr int SM_T    = 23 * UNIT;
constexpr int SM_MISC = SM_T + 4 * KB;
constexpr int SM_END  = SM_MISC + 2464;
constexpr int SLICE_END = 128 + N * 16;
constexpr int X_OUT  = SM_X + UNIT;
constexpr int X_IMG  = X_OUT;
constexpr int X_CNT  = X_IMG + NPC * 64;
constexpr int X_TAB  = X_CNT + NPC * 32 + 128;
constexpr int X_RU   = X_TAB + NPC * 64 + 256;
constexpr int X_DEF  = X_RU + NPC * 4;
constexpr int B_K = 0, B_QK = 32, B_EPO = 40,
              B_A = 48,
              B_F = 176, B_HS = 272, B_Q = 280, B_R = 288,
              B_GO = 296, B_LF = 304, B_TF = 312, B_RGO = 320, B_CGO = 328, B_MI = 336, B_HR = 344,
              B_Z = 352, B_RND = 360,
              B_FA = 416, B_XF = 448, B_SENT = 456, B_S = 464;
constexpr int MI_EPOCH = 488, MI_SLOW = 492, MI_EBAD = 496, MI_NOVF = 500, MI_FLAGS = 504;
constexpr int MI_OVF  = 512;
constexpr int MI_ES   = 768;
constexpr int MI_PCNT = 1792;
constexpr int MI_DIS  = 2304;
constexpr int A0 = 0, A1 = 4, A2 = 8, A3 = 12, A4 = 16, A5 = 19;
constexpr uint32_t A_TILES = A3 | A1 << 8 | A2 << 16 | A0 << 24;
#define PROMO CU_TENSOR_MAP_L2_PROMOTION_L2_128B
#define WH 0
#define WHINT ""
#define GSENT 1
#define LDIDX ld_relaxed4
#define MPF 1
#define P0LATE 0
#define POLL2 0
#define EFETCH 1
#define HPER 200
#define HRW 0
#define T0BAR B_CGO
#define LROW 0

#define RPER 500
constexpr uint32_t W_OVF = 1u << 14, W_EBAD = 1u << 15, W_VALID = 1u << 16, W_KEEP = 0x07fe3fffu;

__device__ uint4         g_cells[RCTA * NCTA * 8];
__device__ uint4         g_H[32 * N];
__device__ uint4         g_idx[NSET * 32];
__device__ __nv_bfloat16 g_M[D * D];
__device__ uint32_t      g_sync[20 * 32];
constexpr int SY_M = 16 * 32, SY_H = 17 * 32, SY_L = 18 * 32, SY_R = 19 * 32;
#define PROF(i) do {} while (0)
#define PROF_FLUSH() do {} while (0)
constexpr int SM_ALLOC = SM_END;
static_assert(SM_ALLOC <= 232448, "shared memory");

struct Params {
    const int* src; const int* dst;
    uint32_t* sync;
    const int* esrc; const int* edst;
    int Efast, chunk;
    const __nv_bfloat16* dis;
    uint4* cells; const char* x; uint2* M;
    int force_slow, force_eslow;
    uint4* idx; uint4* H; uint4* out;
    int E, Ee;
};

__device__ __forceinline__ uint32_t s32(const void* p) { return (uint32_t)__cvta_generic_to_shared(p); }
__device__ __forceinline__ void mbar_init(uint32_t a, uint32_t cnt) { asm volatile("mbarrier.init.shared.b64 [%0], %1;" :: "r"(a), "r"(cnt) : "memory"); }
__device__ __forceinline__ void mbar_arrive(uint32_t a) { asm volatile("mbarrier.arrive.shared.b64 _, [%0];" :: "r"(a) : "memory"); }
__device__ __forceinline__ void mbar_expect(uint32_t a, uint32_t bytes) { asm volatile("mbarrier.arrive.expect_tx.shared.b64 _, [%0], %1;" :: "r"(a), "r"(bytes) : "memory"); }
__device__ __forceinline__ void mbar_wait(uint32_t a, uint32_t parity) {
    uint32_t ok = 0;
#pragma unroll 1
    for (int it = 0; it < SPIN_LIMIT && !ok; ++it)
        asm volatile("{\n.reg .pred p;\nmbarrier.try_wait.parity.shared.b64 p, [%1], %2" WHINT ";\nselp.u32 %0, 1, 0, p;\n}"
                     : "=r"(ok) : "r"(a), "r"(parity) : "memory");
}
__device__ __forceinline__ bool elect() { uint32_t r; asm volatile("{\n.reg .pred p;\nelect.sync _|p, 0xffffffff;\nselp.u32 %0, 1, 0, p;\n}" : "=r"(r) :: "memory"); return r; }
__device__ __forceinline__ void warp_arrive(uint32_t a) {
    asm volatile("{\n.reg .pred p;\nelect.sync _|p, 0xffffffff;\n@p mbarrier.arrive.shared.b64 _, [%0];\n}" :: "r"(a) : "memory");
}
__device__ __forceinline__ void bar_sync(int id, int n)   { __syncwarp(); asm volatile("bar.sync %0, %1;"   :: "r"(id), "r"(n) : "memory"); }
__device__ __forceinline__ void bar_arrive(int id, int n) { __syncwarp(); asm volatile("bar.arrive %0, %1;" :: "r"(id), "r"(n) : "memory"); }
__device__ __forceinline__ void fence_async_smem() { asm volatile("fence.proxy.async.shared::cta;" ::: "memory"); }
__device__ __forceinline__ void fence_async_gmem() { asm volatile("fence.proxy.async.global;" ::: "memory"); }
__device__ __forceinline__ void tma2d(uint32_t dst, const CUtensorMap* tm, int c0, int c1, uint32_t bar) {
    asm volatile("cp.async.bulk.tensor.2d.shared::cluster.global.mbarrier::complete_tx::bytes [%0], [%1, {%3, %4}], [%2];"
                 :: "r"(dst), "l"(tm), "r"(bar), "r"(c0), "r"(c1) : "memory");
}
__device__ __forceinline__ void tma3d(uint32_t dst, const CUtensorMap* tm, int row, uint32_t bar) {
    asm volatile("cp.async.bulk.tensor.3d.shared::cluster.global.mbarrier::complete_tx::bytes [%0], [%1, {%4, %3, %4}], [%2];"
                 :: "r"(dst), "l"(tm), "r"(bar), "r"(row), "r"(0) : "memory");
}
__device__ __forceinline__ void tma2d_store(const CUtensorMap* tm, uint32_t src, int c0, int c1) {
    asm volatile("cp.async.bulk.tensor.2d.global.shared::cta.bulk_group [%0, {%2, %3}], [%1];"
                 :: "l"(tm), "r"(src), "r"(c0), "r"(c1) : "memory");
}
__device__ __forceinline__ void tma2d_add(const CUtensorMap* tm, uint32_t src, int c0, int c1) {
    asm volatile("cp.reduce.async.bulk.tensor.2d.global.shared::cta.add.bulk_group [%0, {%2, %3}], [%1];"
                 :: "l"(tm), "r"(src), "r"(c0), "r"(c1) : "memory");
}
__device__ __forceinline__ void bulk_load(uint32_t dst, const void* src, uint32_t bytes, uint32_t bar) {
    asm volatile("cp.async.bulk.shared::cluster.global.mbarrier::complete_tx::bytes [%0], [%1], %2, [%3];"
                 :: "r"(dst), "l"(src), "r"(bytes), "r"(bar) : "memory");
}
__device__ __forceinline__ void bulk_store(void* dst, uint32_t src, uint32_t bytes) {
    asm volatile("cp.async.bulk.global.shared::cta.bulk_group [%0], [%1], %2;" :: "l"(dst), "r"(src), "r"(bytes) : "memory");
}
__device__ __forceinline__ uint32_t clk() { uint32_t c; asm volatile("mov.u32 %0, %%clock;" : "=r"(c) :: "memory"); return c; }
__device__ __forceinline__ void wait_clk(uint32_t t) { while ((int)(clk() - t) < 0) {} }
__device__ __forceinline__ void bulk_commit() { asm volatile("cp.async.bulk.commit_group;" ::: "memory"); }
template <int K> __device__ __forceinline__ void bulk_wait_read() { asm volatile("cp.async.bulk.wait_group.read %0;" :: "n"(K) : "memory"); }
__device__ __forceinline__ void prefetch_map(const CUtensorMap* tm) { asm volatile("prefetch.tensormap [%0];" :: "l"(tm) : "memory"); }
__device__ __forceinline__ uint4 lds128(uint32_t a) { uint4 v; asm volatile("ld.shared.v4.u32 {%0,%1,%2,%3}, [%4];" : "=r"(v.x), "=r"(v.y), "=r"(v.z), "=r"(v.w) : "r"(a) : "memory"); return v; }
__device__ __forceinline__ void sts128(uint32_t a, uint4 v) { asm volatile("st.shared.v4.u32 [%0], {%1,%2,%3,%4};" :: "r"(a), "r"(v.x), "r"(v.y), "r"(v.z), "r"(v.w) : "memory"); }
__device__ __forceinline__ uint32_t lds32(uint32_t a) { uint32_t v; asm volatile("ld.shared.u32 %0, [%1];" : "=r"(v) : "r"(a) : "memory"); return v; }
__device__ __forceinline__ void sts32(uint32_t a, uint32_t v) { asm volatile("st.shared.u32 [%0], %1;" :: "r"(a), "r"(v) : "memory"); }
__device__ __forceinline__ void sts16(uint32_t a, uint32_t v) { asm volatile("st.shared.u16 [%0], %1;" :: "r"(a), "h"((unsigned short)v) : "memory"); }
__device__ __forceinline__ uint32_t atoms_add(uint32_t a, uint32_t x) { uint32_t v; asm volatile("atom.shared.add.u32 %0, [%1], %2;" : "=r"(v) : "r"(a), "r"(x) : "memory"); return v; }
__device__ __forceinline__ uint32_t ld_relaxed(const uint32_t* p) { uint32_t v; asm volatile("ld.relaxed.gpu.global.u32 %0, [%1];" : "=r"(v) : "l"(p) : "memory"); return v; }
__device__ __forceinline__ uint4 ld_relaxed4(const uint4* p) { uint4 v; asm volatile("ld.relaxed.gpu.global.L1::no_allocate.v4.u32 {%0,%1,%2,%3}, [%4];" : "=r"(v.x), "=r"(v.y), "=r"(v.z), "=r"(v.w) : "l"(p) : "memory"); return v; }
__device__ __forceinline__ uint32_t ld_acquire(const uint32_t* p) { uint32_t v; asm volatile("ld.acquire.gpu.global.u32 %0, [%1];" : "=r"(v) : "l"(p) : "memory"); return v; }
__device__ __forceinline__ void st_relaxed(uint32_t* p, uint32_t v) { asm volatile("st.relaxed.gpu.global.u32 [%0], %1;" :: "l"(p), "r"(v) : "memory"); }
__device__ __forceinline__ void red_relaxed(uint32_t* p) { asm volatile("red.relaxed.gpu.global.add.u32 [%0], 1;" :: "l"(p) : "memory"); }
__device__ __forceinline__ uint32_t list_tag(uint32_t epoch) { return (epoch % 3u + 1u) * 0x40004000u; }
__device__ __forceinline__ void red_release(uint32_t* p) { asm volatile("red.release.gpu.global.add.u32 [%0], 1;" :: "l"(p) : "memory"); }
__device__ __forceinline__ void wait_count(const uint32_t* p, uint32_t target) {
#pragma unroll 1
    for (int it = 0; it < SPIN_LIMIT; ++it)
        if ((int)(ld_acquire(p) - target) >= 0) break;
}
__device__ __forceinline__ bool mbar_test(uint32_t a, uint32_t parity) {
    uint32_t ok;
    asm volatile("{\n.reg .pred p;\nmbarrier.test_wait.parity.shared.b64 p, [%1], %2;\nselp.u32 %0, 1, 0, p;\n}" : "=r"(ok) : "r"(a), "r"(parity) : "memory");
    return __all_sync(0xffffffffu, ok);
}
__device__ __forceinline__ uint4 ldg_in(const void* p) { uint4 v; asm volatile("ld.global.nc.L1::no_allocate.v4.u32 {%0,%1,%2,%3}, [%4];" : "=r"(v.x), "=r"(v.y), "=r"(v.z), "=r"(v.w) : "l"(p)); return v; }
__device__ __forceinline__ uint4 ldg_sc(const void* p) { uint4 v; asm volatile("ld.global.L1::no_allocate.v4.u32 {%0,%1,%2,%3}, [%4];" : "=r"(v.x), "=r"(v.y), "=r"(v.z), "=r"(v.w) : "l"(p) : "memory"); return v; }
__device__ __forceinline__ void red_row(uint4* p, uint4 v) { asm volatile("red.relaxed.gpu.global.add.noftz.v4.bf16x2 [%0], {%1,%2,%3,%4};" :: "l"(p), "r"(v.x), "r"(v.y), "r"(v.z), "r"(v.w) : "memory"); }
__device__ __forceinline__ uint32_t pack_bf16(float lo, float hi) { uint32_t r; asm("cvt.rn.bf16x2.f32 %0, %1, %2;" : "=r"(r) : "f"(hi), "f"(lo)); return r; }
__device__ __forceinline__ float blo(uint32_t v) { return __uint_as_float(v << 16); }
__device__ __forceinline__ float bhi(uint32_t v) { return __uint_as_float(v & 0xffff0000u); }
__device__ __forceinline__ uint32_t movm(uint32_t a) { uint32_t d; asm volatile("movmatrix.sync.aligned.m8n8.trans.b16 %0, %1;" : "=r"(d) : "r"(a)); return d; }
__device__ __forceinline__ const char* row_ptr(const char* base, uint32_t row) {
    uint64_t r; asm("mad.wide.u32 %0, %1, 512, %2;" : "=l"(r) : "r"(row), "l"((uint64_t)base)); return (const char*)r;
}

constexpr uint32_t DESC_HI = 64u | (1u << 30);
__device__ __forceinline__ uint32_t desc_lo(uint32_t addr) { return ((addr & 0x3FFFF) >> 4) | (1u << 16); }
__device__ __forceinline__ void wg_fence()  { asm volatile("wgmma.fence.sync.aligned;" ::: "memory"); }
__device__ __forceinline__ void wg_commit() { asm volatile("wgmma.commit_group.sync.aligned;" ::: "memory"); }
template <int K> __device__ __forceinline__ void wg_wait() { asm volatile("wgmma.wait_group.sync.aligned %0;" :: "n"(K) : "memory"); }
#define GK_ACC(c) c(d[0]), c(d[1]), c(d[2]), c(d[3]), c(d[4]), c(d[5]), c(d[6]), c(d[7]), c(d[8]), c(d[9]), \
    c(d[10]), c(d[11]), c(d[12]), c(d[13]), c(d[14]), c(d[15]), c(d[16]), c(d[17]), c(d[18]), c(d[19]), \
    c(d[20]), c(d[21]), c(d[22]), c(d[23]), c(d[24]), c(d[25]), c(d[26]), c(d[27]), c(d[28]), c(d[29]), \
    c(d[30]), c(d[31]), c(d[32]), c(d[33]), c(d[34]), c(d[35]), c(d[36]), c(d[37]), c(d[38]), c(d[39])
#define GK_WGMMA(P) "{\n.reg .pred p;\n.reg .b64 da, db;\nsetp.ne.b32 p, " P ", 0;\nmov.b64 da, {%40, %42};\nmov.b64 db, {%41, %42};\n" \
    "wgmma.mma_async.sync.aligned.m64n80k16.f32.bf16.bf16 " \
    "{%0,%1,%2,%3,%4,%5,%6,%7,%8,%9,%10,%11,%12,%13,%14,%15,%16,%17,%18,%19," \
    "%20,%21,%22,%23,%24,%25,%26,%27,%28,%29,%30,%31,%32,%33,%34,%35,%36,%37,%38,%39}, da, db, p, 1, 1, 1, 0;\n}\n"
template <bool FIRST>
__device__ __forceinline__ void wgmma80(float (&d)[40], uint32_t alo, uint32_t blo_) {
    if (FIRST) asm volatile(GK_WGMMA("0") : GK_ACC("=f") : "r"(alo), "r"(blo_), "r"(DESC_HI));
    else       asm volatile(GK_WGMMA("1") : GK_ACC("+f") : "r"(alo), "r"(blo_), "r"(DESC_HI));
}
template <int KQ>
__device__ __forceinline__ void gemm_quarter(float (&d)[40], uint32_t unit, uint32_t tile, uint32_t bar, uint32_t parity, uint32_t rel = 0) {
    mbar_wait(bar + KQ * 8, parity);
    __syncwarp();
    const uint32_t a = desc_lo(unit), b = desc_lo(tile) + ((KQ * KB) >> 4);
    wg_fence();
    wgmma80<KQ == 0>(d, a, b);
    if (KQ) { wg_commit(); wg_wait<1>(); warp_arrive(rel); }
    wgmma80<false>(d, a + 128, b + 2);
    wgmma80<false>(d, a + 256, b + 4);
    wgmma80<false>(d, a + 384, b + 6);
    wg_commit();
}
__device__ __forceinline__ void stsm4t(uint32_t a, uint32_t r0, uint32_t r1, uint32_t r2, uint32_t r3) {
    asm volatile("stmatrix.sync.aligned.m8n8.x4.trans.shared.b16 [%0], {%1,%2,%3,%4};" :: "r"(a), "r"(r0), "r"(r1), "r"(r2), "r"(r3) : "memory");
}
__device__ __forceinline__ void stsm4(uint32_t a, uint32_t r0, uint32_t r1, uint32_t r2, uint32_t r3) {
    asm volatile("stmatrix.sync.aligned.m8n8.x4.shared.b16 [%0], {%1,%2,%3,%4};" :: "r"(a), "r"(r0), "r"(r1), "r"(r2), "r"(r3) : "memory");
}
__device__ __forceinline__ uint4 ldsm4(uint32_t a) {
    uint4 v; asm volatile("ldmatrix.sync.aligned.m8n8.x4.shared.b16 {%0,%1,%2,%3}, [%4];" : "=r"(v.x), "=r"(v.y), "=r"(v.z), "=r"(v.w) : "r"(a) : "memory"); return v;
}
__device__ __forceinline__ void stsm2t(uint32_t a, uint32_t r0, uint32_t r1) {
    asm volatile("stmatrix.sync.aligned.m8n8.x2.trans.shared.b16 [%0], {%1,%2};" :: "r"(a), "r"(r0), "r"(r1) : "memory");
}
__device__ __forceinline__ void mma16816(float (&c)[4], uint32_t a0, uint32_t a1, uint32_t a2, uint32_t a3, uint32_t b0, uint32_t b1) {
    asm volatile("mma.sync.aligned.m16n8k16.row.col.f32.bf16.bf16.f32 {%0,%1,%2,%3}, {%4,%5,%6,%7}, {%8,%9}, {%0,%1,%2,%3};"
        : "+f"(c[0]), "+f"(c[1]), "+f"(c[2]), "+f"(c[3]) : "r"(a0), "r"(a1), "r"(a2), "r"(a3), "r"(b0), "r"(b1));
}
__device__ __forceinline__ void pack_acc(uint32_t (&h)[20], const float (&d)[40]) {
#pragma unroll
    for (int i = 0; i < 20; ++i) h[i] = pack_bf16(d[2 * i], d[2 * i + 1]);
}
__device__ __forceinline__ void store_tile(const uint32_t (&h)[20], uint32_t tile, int mt, int w4, int lane) {
    const int r = lane & 7;
    const uint32_t base = tile + mt * KB + (((lane >> 4) * 8 + r) * 128) + (((2 * w4 + ((lane >> 3) & 1)) ^ r) << 4);
#pragma unroll
    for (int i = 0; i < 5; ++i) stsm4t(base + i * 2048, h[4 * i], h[4 * i + 1], h[4 * i + 2], h[4 * i + 3]);
}
__device__ __forceinline__ void fma8(float (&a)[8], float w, const uint4& v) {
    a[0] = fmaf(w, blo(v.x), a[0]); a[1] = fmaf(w, bhi(v.x), a[1]);
    a[2] = fmaf(w, blo(v.y), a[2]); a[3] = fmaf(w, bhi(v.y), a[3]);
    a[4] = fmaf(w, blo(v.z), a[4]); a[5] = fmaf(w, bhi(v.z), a[5]);
    a[6] = fmaf(w, blo(v.w), a[6]); a[7] = fmaf(w, bhi(v.w), a[7]);
}
__device__ __forceinline__ float dot8(const float (&q)[8], const uint4& v) {
    float s = q[0] * blo(v.x);
    s = fmaf(q[1], bhi(v.x), s); s = fmaf(q[2], blo(v.y), s); s = fmaf(q[3], bhi(v.y), s);
    s = fmaf(q[4], blo(v.z), s); s = fmaf(q[5], bhi(v.z), s); s = fmaf(q[6], blo(v.w), s); s = fmaf(q[7], bhi(v.w), s);
    return s;
}
__device__ __forceinline__ uint4 pack8(const float (&a)[8], float s) {
    return make_uint4(pack_bf16(a[0] * s, a[1] * s), pack_bf16(a[2] * s, a[3] * s), pack_bf16(a[4] * s, a[5] * s), pack_bf16(a[6] * s, a[7] * s));
}
__device__ __forceinline__ uint32_t tile_chunk(uint32_t tile, int r, int c) {
    return tile + (c >> 3) * KB + r * 128 + (((c & 7) ^ (r & 7)) << 4);
}
__device__ __forceinline__ uint32_t wsum4(const uint32_t (&a)[4], uint32_t r0, uint32_t r1, uint32_t r2, uint32_t r3) {
    uint32_t z;
    asm("{\n.reg .b32 t;\nmul.rn.bf16x2 t, %1, %5;\nfma.rn.bf16x2 t, %2, %6, t;\nfma.rn.bf16x2 t, %3, %7, t;\nfma.rn.bf16x2 %0, %4, %8, t;\n}"
        : "=r"(z) : "r"(a[0]), "r"(a[1]), "r"(a[2]), "r"(a[3]), "r"(r0), "r"(r1), "r"(r2), "r"(r3));
    return z;
}
__device__ __forceinline__ void softmax4(const float (&s)[4], const float (&u)[4], int lane, uint32_t (&a)[4]) {
    const bool b = lane & 4, c = lane & 8;
    const float k0 = (b ? u[1] : s[0]) + __shfl_xor_sync(0xffffffffu, b ? s[1] : u[0], 4);
    const float k1 = (b ? u[3] : s[2]) + __shfl_xor_sync(0xffffffffu, b ? s[3] : u[2], 4);
    const float e = (c ? k1 : k0) + __shfl_xor_sync(0xffffffffu, c ? k0 : k1, 9);
    float pe;
    asm("ex2.approx.ftz.f32 %0, %1;" : "=f"(pe) : "f"(e * (0.0625f * 1.4426950408889634f)));
    const int l0 = (lane >> 4) * 18;
    const float p0 = __shfl_sync(0xffffffffu, pe, l0), p1 = __shfl_sync(0xffffffffu, pe, l0 + 9);
    const float p2 = __shfl_sync(0xffffffffu, pe, l0 + 4), p3 = __shfl_sync(0xffffffffu, pe, l0 + 13);
    float inv;
    asm("rcp.approx.ftz.f32 %0, %1;" : "=f"(inv) : "f"(((p0 + p1) + (p2 + p3)) + 1e-9f));
    a[0] = pack_bf16(p0 * inv, p0 * inv); a[1] = pack_bf16(p1 * inv, p1 * inv);
    a[2] = pack_bf16(p2 * inv, p2 * inv); a[3] = pack_bf16(p3 * inv, p3 * inv);
}
__device__ __forceinline__ void attention_chunks(const uint4 (&r)[4][2], uint32_t tile, int node, int lane) {
    const uint32_t qa = tile_chunk(tile, node + (lane >> 4), lane & 15);
    const uint4 q0 = lds128(qa), q1 = lds128(qa + 2 * KB);
    float s[4] = {0.f, 0.f, 0.f, 0.f}, u[4] = {0.f, 0.f, 0.f, 0.f};
    mma16816(s, r[0][0].x, r[1][0].x, r[0][0].y, r[1][0].y, q0.x, q0.y); mma16816(u, r[2][0].x, r[3][0].x, r[2][0].y, r[3][0].y, q0.x, q0.y);
    mma16816(s, r[0][0].z, r[1][0].z, r[0][0].w, r[1][0].w, q0.z, q0.w); mma16816(u, r[2][0].z, r[3][0].z, r[2][0].w, r[3][0].w, q0.z, q0.w);
    mma16816(s, r[0][1].x, r[1][1].x, r[0][1].y, r[1][1].y, q1.x, q1.y); mma16816(u, r[2][1].x, r[3][1].x, r[2][1].y, r[3][1].y, q1.x, q1.y);
    mma16816(s, r[0][1].z, r[1][1].z, r[0][1].w, r[1][1].w, q1.z, q1.w); mma16816(u, r[2][1].z, r[3][1].z, r[2][1].w, r[3][1].w, q1.z, q1.w);
    uint32_t a[4];
    softmax4(s, u, lane, a);
#pragma unroll
    for (int h = 0; h < 2; ++h)
        sts128(qa + h * 2 * KB, make_uint4(wsum4(a, r[0][h].x, r[1][h].x, r[2][h].x, r[3][h].x), wsum4(a, r[0][h].y, r[1][h].y, r[2][h].y, r[3][h].y),
                                           wsum4(a, r[0][h].z, r[1][h].z, r[2][h].z, r[3][h].z), wsum4(a, r[0][h].w, r[1][h].w, r[2][h].w, r[3][h].w)));
}
__device__ __forceinline__ void attention_frags(const uint4 (&r)[2][4], uint32_t tile, int node, int lane) {
    const int nd = node + ((lane >> 2) & 1);
    const uint32_t qa = tile + (lane >> 4) * KB + nd * 128 + (((lane ^ (lane >> 1 & 4) ^ nd) & 7) << 4);
    const uint4 q0 = ldsm4(qa), q1 = ldsm4(qa + 2 * KB);
    float s[4] = {0.f, 0.f, 0.f, 0.f}, u[4] = {0.f, 0.f, 0.f, 0.f};
    mma16816(s, r[0][0].x, r[0][0].y, r[0][0].z, r[0][0].w, q0.x, q0.y); mma16816(u, r[1][0].x, r[1][0].y, r[1][0].z, r[1][0].w, q0.x, q0.y);
    mma16816(s, r[0][1].x, r[0][1].y, r[0][1].z, r[0][1].w, q0.z, q0.w); mma16816(u, r[1][1].x, r[1][1].y, r[1][1].z, r[1][1].w, q0.z, q0.w);
    mma16816(s, r[0][2].x, r[0][2].y, r[0][2].z, r[0][2].w, q1.x, q1.y); mma16816(u, r[1][2].x, r[1][2].y, r[1][2].z, r[1][2].w, q1.x, q1.y);
    mma16816(s, r[0][3].x, r[0][3].y, r[0][3].z, r[0][3].w, q1.z, q1.w); mma16816(u, r[1][3].x, r[1][3].y, r[1][3].z, r[1][3].w, q1.z, q1.w);
    uint32_t a[4];
    softmax4(s, u, lane, a);
#pragma unroll
    for (int h = 0; h < 2; ++h)
        stsm4(qa + h * 2 * KB, wsum4(a, r[0][2 * h].x, r[0][2 * h].y, r[1][2 * h].x, r[1][2 * h].y), wsum4(a, r[0][2 * h].z, r[0][2 * h].w, r[1][2 * h].z, r[1][2 * h].w),
              wsum4(a, r[0][2 * h + 1].x, r[0][2 * h + 1].y, r[1][2 * h + 1].x, r[1][2 * h + 1].y), wsum4(a, r[0][2 * h + 1].z, r[0][2 * h + 1].w, r[1][2 * h + 1].z, r[1][2 * h + 1].w));
}
__device__ __noinline__ void attention_generic(const Params& p, uint32_t tile, int nl, int node, int lane) {
    const uint32_t qa = tile_chunk(tile, nl, lane);
    const uint4 qv = lds128(qa);
    const float q[8] = {blo(qv.x), bhi(qv.x), blo(qv.y), bhi(qv.y), blo(qv.z), bhi(qv.z), blo(qv.w), bhi(qv.w)};
    float z[8] = {0.f, 0.f, 0.f, 0.f, 0.f, 0.f, 0.f, 0.f};
    float den = 0.f;
#pragma unroll 1
    for (int e = 0; e < p.Ee; e += 32) {
        const bool m = (e + lane < p.Ee) && (__ldg(p.edst + e + lane) == node);
        const int sv = m ? __ldg(p.esrc + e + lane) : 0;
        uint32_t bal = __ballot_sync(0xffffffffu, m);
        while (bal) {
            const int l = __ffs(bal) - 1; bal &= bal - 1;
            const uint4 v = ldg_in(row_ptr(p.x + lane * 16, __shfl_sync(0xffffffffu, sv, l)));
            float c = dot8(q, v);
#pragma unroll
            for (int o = 16; o; o >>= 1) c += __shfl_xor_sync(0xffffffffu, c, o);
            const float pe = expf(c * 0.0625f);
            den += pe;
            fma8(z, pe, v);
        }
    }
    sts128(qa, pack8(z, 1.f / (den + 1e-9f)));
}
__device__ __noinline__ void local_generic(const Params& p, int node0, int w, int lane) {
    float a0[8], a1[8], a2[8], a3[8];
#pragma unroll
    for (int k = 0; k < 8; ++k) { a0[k] = 0.f; a1[k] = 0.f; a2[k] = 0.f; a3[k] = 0.f; }
#pragma unroll 1
    for (int e = 0; e < p.E; e += 32) {
        const int dl = (e + lane < p.E) ? __ldg(p.dst + e + lane) - node0 - w : -1;
        const int k = dl == 0 ? 0 : dl == AW ? 1 : dl == 2 * AW ? 2 : (dl == 3 * AW && w + 3 * AW < NPC) ? 3 : -1;
        const int sv = k >= 0 ? __ldg(p.src + e + lane) : 0;
        uint32_t bal = __ballot_sync(0xffffffffu, k >= 0);
        while (bal) {
            const int l = __ffs(bal) - 1; bal &= bal - 1;
            const int s = __shfl_sync(0xffffffffu, sv, l), kk = __shfl_sync(0xffffffffu, k, l);
            const uint4 v = ldg_sc(p.H + lane * N + s);
            if (kk & 2) { if (kk & 1) fma8(a3, 1.f, v); else fma8(a2, 1.f, v); }
            else        { if (kk & 1) fma8(a1, 1.f, v); else fma8(a0, 1.f, v); }
        }
    }
    const int n = node0 + w;
    red_row(p.out + n * 32 + lane, pack8(a0, __bfloat162float(p.dis[n])));
    red_row(p.out + (n + AW) * 32 + lane, pack8(a1, __bfloat162float(p.dis[n + AW])));
    red_row(p.out + (n + 2 * AW) * 32 + lane, pack8(a2, __bfloat162float(p.dis[n + 2 * AW])));
    if (w + 3 * AW < NPC) red_row(p.out + (n + 3 * AW) * 32 + lane, pack8(a3, __bfloat162float(p.dis[n + 3 * AW])));
}
template <int HI>
__device__ __forceinline__ void agg_step(float (&c)[4], uint32_t w, uint32_t base, uint32_t dg) {
    uint32_t a, r0, r1, r2, r3;
    if (HI) asm("dp2a.hi.u32.u32 %0, %1, %2, %3;" : "=r"(a) : "r"(w), "r"(0x10000010u), "r"(base));
    else    asm("dp2a.lo.u32.u32 %0, %1, %2, %3;" : "=r"(a) : "r"(w), "r"(0x10000010u), "r"(base));
    asm volatile("ldmatrix.sync.aligned.m8n8.x4.trans.shared.b16 {%0,%1,%2,%3}, [%4];" : "=r"(r0), "=r"(r1), "=r"(r2), "=r"(r3) : "r"(a));
    mma16816(c, r0, r1, r2, r3, dg, dg);
}
struct Unit { uint4 a, b; };
__device__ __forceinline__ void agg_tail(float (&c)[4], const uint4& w, uint32_t base, uint32_t dg, uint32_t lt) {
    if (__any_sync(0xffffffffu, w.z > (lt | 0xffffu))) {
        agg_step<1>(c, w.z, base, dg);
        if (__any_sync(0xffffffffu, w.w & 0x3fffu)) agg_step<0>(c, w.w, base, dg);
    }
}
__device__ __forceinline__ uint32_t unit_stale(const Unit& x, uint32_t lt) {
    const uint32_t o = x.a.x | x.a.y | x.a.z | x.a.w | x.b.x | x.b.y | x.b.z | x.b.w, a = x.a.x & x.a.y & x.a.z & x.a.w & x.b.x & x.b.y & x.b.z & x.b.w;
    return ((o ^ lt) | (a ^ lt)) & 0xc000u;
}
__device__ __forceinline__ void agg_unit(const Unit& x, uint32_t base, uint32_t dsel, uint32_t stg, uint32_t lt) {
    float ca[4] = {0.f, 0.f, 0.f, 0.f}, cb[4] = {0.f, 0.f, 0.f, 0.f};
    const uint32_t da = __byte_perm(x.a.w, 0, dsel), db = __byte_perm(x.b.w, 0, dsel);
    agg_step<0>(ca, x.a.x, base, da); agg_step<0>(cb, x.b.x, base, db);
    agg_step<1>(ca, x.a.x, base, da); agg_step<1>(cb, x.b.x, base, db);
    agg_step<0>(ca, x.a.y, base, da); agg_step<0>(cb, x.b.y, base, db);
    agg_step<1>(ca, x.a.y, base, da); agg_step<1>(cb, x.b.y, base, db);
    agg_step<0>(ca, x.a.z, base, da); agg_step<0>(cb, x.b.z, base, db);
    agg_tail(ca, x.a, base, da, lt);
    agg_tail(cb, x.b, base, db, lt);
    stsm2t(stg, pack_bf16(ca[0] + ca[2], ca[1] + ca[3]), pack_bf16(cb[0] + cb[2], cb[1] + cb[3]));
}

__global__ void __launch_bounds__(NTHR, 1)
fused_kernel(const __grid_constant__ Params p,
             const __grid_constant__ CUtensorMap tmX, const __grid_constant__ CUtensorMap tmWl,
             const __grid_constant__ CUtensorMap tmM, const __grid_constant__ CUtensorMap tmWv,
             const __grid_constant__ CUtensorMap tmR, const __grid_constant__ CUtensorMap tmO,
             const __grid_constant__ CUtensorMap tmG, const __grid_constant__ CUtensorMap tmQ,
             const __grid_constant__ CUtensorMap tmK)
{
    extern __shared__ __align__(1024) unsigned char smem[];
    const uint32_t sb = s32(smem);
    const int tid = threadIdx.x, lane = tid & 31;
    const int warp = __shfl_sync(0xffffffffu, tid >> 5, 0);
    const int cta = blockIdx.x;
    const int node0 = cta * NPC;
    const bool rowcta = cta < RCTA;
    const int slice = cta >> 2, quarter = cta & 3;
    const int nlast = 12 + (quarter == 3);
    const int i0 = (cta >> 3) * 16, j0 = (cta & 7) * 32;
    const uint32_t bars = sb + SM_MISC;
    const uint32_t sS = sb + SM_S, sT = sb + SM_T;

    const bool stage = rowcta && !p.force_eslow;
    auto publish = [&](int set) {
        const uint4 dv = lds128(bars + MI_DIS + set * 16);
        uint4 v = lds128(sb + X_IMG + set * 512 + lane * 16);
        const uint4 z = lds128(sb + X_DEF + set * 64 + (lane & 3) * 16);
        if ((lane & 3) == 3) { v.x = __byte_perm(v.x, v.y, 0x5410); v.y = v.w; }
        v.x = __vmaxu2(v.x, z.x); v.y = __vmaxu2(v.y, z.y); v.z = __vmaxu2(v.z, z.z); v.w = __vmaxu2(v.w, z.w);
        if (lds32(bars + MI_SLOW)) v = make_uint4(0, 0, 0, 0);
        const uint32_t lt = list_tag(lds32(bars + MI_EPOCH));
        v.x |= lt; v.y |= lt; v.z |= lt; v.w |= lt;
        if ((lane & 3) == 3) { const uint32_t sel = lane & 16 ? 0x7632 : 0x5410; v.z = __byte_perm(dv.x, dv.y, sel); v.w = __byte_perm(dv.z, dv.w, sel); }
        uint32_t* ip = (uint32_t*)p.idx + (cta * 10 + set) * 128 + lane;
        st_relaxed(ip, __byte_perm(v.x, v.z, 0x5410));      st_relaxed(ip + 32, __byte_perm(v.x, v.z, 0x7632));
        st_relaxed(ip + 64, __byte_perm(v.y, v.w, 0x5410)); st_relaxed(ip + 96, __byte_perm(v.y, v.w, 0x7632));
    };

    if (warp >= AW) {
        const int pw = warp - AW;
        if (elect()) {
            auto init = [&](int b0, int b1, int c) {
#pragma unroll
                for (int b = b0; b < b1; b += 8) mbar_init(bars + b, c);
            };
            if (pw == 0)      { PROF(0); prefetch_map(&tmQ); prefetch_map(&tmK); prefetch_map(&tmX); prefetch_map(&tmWl); init(B_K, B_A, 1); }
            else if (pw == 1) { init(B_A, B_F, 4); mbar_init(bars + B_S, 6); }
            else if (pw == 2) { init(B_F, B_GO, GW); init(B_XF, B_S, 8); }
            else              { init(B_GO, B_Z, 1); init(B_Z, B_RND + 48, AW); mbar_init(bars + B_RND + 48, nlast); init(B_FA, B_XF, 8); }
            asm volatile("fence.mbarrier_init.release.cluster;" ::: "memory");
        }
        bar_arrive(4, LT + 128);
        if (pw) bar_sync(0, GT + 128); else bar_arrive(0, GT + 128);
        auto load_units = [&](const CUtensorMap* tm, int kq, int slot) {
            if (elect()) { mbar_expect(bars + B_K + kq * 8, 4 * UNIT); tma3d(sS + slot * UNIT, tm, kq * 64, bars + B_K + kq * 8); }
        };
        auto stage_tiles = [&](int c) {
            if (!stage) return;
            const int v0 = pw ? pw - 2 : 2;
            uint4 e[6];
#pragma unroll
            for (int n = 0; n < 6; ++n) { const int v = min(v0 + 3 * n, 15); e[n] = lds128(bars + MI_ES + ((v >> 2) * 16 + c * 4 + (v & 3)) * 16); }
            mbar_wait(bars + (c ? B_F + 32 + c * 8 : T0BAR), 0);
            if (elect()) {
#pragma unroll
                for (int n = 0; n < 6; ++n) {
                    const int v = v0 + 3 * n;
                    if (n < 5 || v < 16) {
                        const uint32_t dst = sS + (A_TILES >> (8 * c) & 255) * UNIT + v * 2048, bar = bars + B_A + ((v & 12) + c) * 8;
                        mbar_expect(bar, 2048);
                        tma2d(dst, &tmG, 0, e[n].x, bar);        tma2d(dst + 512, &tmG, 0, e[n].y, bar);
                        tma2d(dst + 1024, &tmG, 0, e[n].z, bar); tma2d(dst + 1536, &tmG, 0, e[n].w, bar);
                    }
                }
            }
            if (pw == 2 && lane == 0) PROF(45 + c);
        };
        if (pw == 0) {
            if (elect()) {
                mbar_expect(bars + B_QK, 3 * UNIT);
                tma3d(sS + A3 * UNIT, &tmQ, i0, bars + B_QK);
                tma3d(sS + (A3 + 1) * UNIT, &tmK, j0, bars + B_QK);
                if (rowcta) {
#pragma unroll
                    for (int kq = 0; kq < 4; ++kq) {
                        mbar_expect(bars + B_K + kq * 8, KB + 4 * UNIT);
                        tma2d(sT + kq * KB, &tmX, kq * 64, node0, bars + B_K + kq * 8);
                        tma3d(sS + (kq == 0 ? A0 : kq == 1 ? A1 : kq == 2 ? A2 : A4) * UNIT, &tmWl, kq * 64, bars + B_K + kq * 8);
                    }
                    PROF(3);
                    prefetch_map(&tmM); prefetch_map(&tmG); prefetch_map(&tmWv); prefetch_map(&tmR);
                }
            }
        }
        if (pw >= 2 && stage) sts128(bars + MI_ES + ((pw - 2) * 32 + lane) * 16, ldg_in(p.esrc + (node0 + 32 * (pw - 2) + lane) * 4));
        if (pw != 1 && rowcta) {
            bar_sync(5, 96);
            mbar_wait(bars + B_EPO, 0);
            mbar_wait(bars + B_F, 0);
#pragma unroll 1
            for (int c = 0; c < 4; ++c) {
                if (pw == 0 && c == P0LATE) {
                    mbar_wait(bars + B_CGO, 0);
                    if (MPF && lane == 0) prefetch_map(&tmM);
                    wait_count(p.sync + SY_M, (lds32(bars + MI_EPOCH) + 1) * NCTA);
                    fence_async_gmem();
                    if (lane == 0) PROF(2);
                    load_units(&tmM, 0, A0);
                    if (lane == 0) PROF(39);
                    mbar_wait(bars + B_F + 8, 0);  load_units(&tmM, 1, A1);
                    mbar_wait(bars + B_F + 16, 0); load_units(&tmM, 2, A2);
                    warp_arrive(bars + B_MI);
                    if (lane == 0) PROF(40);
                }
                if (pw == 0 && c == 1) { mbar_wait(bars + B_F + 32, 0); load_units(&tmM, 3, A0); }
                stage_tiles(c);
            }
        }
        if (pw == 0) {
            if (rowcta) {
                if (HRW) mbar_wait(bars + B_HR, 0);
                mbar_wait(bars + B_FA, 0);      fence_async_smem();  load_units(&tmWv, 0, A3);
                mbar_wait(bars + B_FA + 8, 0);  fence_async_smem();  load_units(&tmWv, 1, A1);
                mbar_wait(bars + B_FA + 16, 0); fence_async_smem();  load_units(&tmWv, 2, A2);
                mbar_wait(bars + B_HR, 0);
                mbar_wait(bars + B_XF, 0);      fence_async_smem();  load_units(&tmWv, 3, A5);
                if (lane == 0) PROF(5);
            }
        } else if (pw == 1) {
            if (rowcta && lane < 10) sts128(bars + MI_DIS + lane * 16, ldg_in(p.dis + node0 + lane * 8));
            bar_sync(3, 128 + 32);
            mbar_wait(bars + B_SENT, 0);
            if (elect()) { PROF(38); red_release(p.sync + SY_M); PROF(1); mbar_arrive(bars + B_CGO); }
            mbar_wait(bars + B_EPO, 0);
            if (rowcta) {
                mbar_wait(bars + B_HS, 0);
                fence_async_smem();
                mbar_wait(bars + B_MI, 0);
                uint32_t tn = clk();
#pragma unroll 1
                for (int s = 0; s < 32; s += 2) {
                    wait_clk(tn); tn += HPER;
                    if (elect()) {
                        bulk_store(p.H + s * N + node0, sS + A4 * UNIT + s * 1280, 1280);
                        bulk_store(p.H + (s + 1) * N + node0, sS + A4 * UNIT + s * 1280 + 1280, 1280);
                    }
                }
                if (elect()) {
                    bulk_commit();
                    asm volatile("cp.async.bulk.wait_group 0;" ::: "memory");
                    PROF(43);
                    fence_async_gmem();
                    red_release(p.sync + SY_H);
                    mbar_arrive(bars + B_HR);
                    PROF(31);
                }
            }
            wait_count(p.sync + SY_H, (lds32(bars + MI_EPOCH) + 1) * RCTA);
            fence_async_gmem();
            if (lane == 0) PROF(6);
            const char* hs = (const char*)(p.H + slice * N) - 128;
            auto chunk = [&](int bar, int lo, int hi) {
                if (rowcta && bar) mbar_wait(bars + bar, 0);
                if (bar >= B_FA) fence_async_smem();
                if (lo == 128) { if (lane < 8) sts128(sS + lane * 16, make_uint4(0, 0, 0, 0)); __syncwarp(); }
                if (elect()) { mbar_expect(bars + B_S, hi - lo); bulk_load(sS + lo, hs + lo, hi - lo, bars + B_S); }
            };
            chunk(0, A4 * UNIT, A5 * UNIT);
            chunk(B_FA + 24, 128, 4 * UNIT);
            chunk(B_F + 64, A3 * UNIT, (A3 + 4) * UNIT);
            chunk(B_F + 72, A1 * UNIT, (A1 + 4) * UNIT);
            chunk(B_F + 80, A2 * UNIT, (A2 + 4) * UNIT);
            chunk(B_F + 88, A5 * UNIT, SLICE_END);
            if (lane == 0) PROF(7);
        } else {
            mbar_wait(bars + B_EPO, 0);
            const uint32_t epoch1 = lds32(bars + MI_EPOCH) + 1;
            if (pw == 2) {
                if (rowcta) {
                    mbar_wait(bars + B_R, 0);
                    fence_async_smem();
                    uint32_t tn = clk();
#pragma unroll 1
                    for (int r = 0; r < NPC; r += 16) {
                        wait_clk(tn); tn += RPER;
                        if (elect()) {
#pragma unroll
                            for (int kb = 0; kb < 4; ++kb) tma2d_store(&tmR, sT + kb * KB + r * 128, kb * 64, node0 + r);
                        }
                    }
                    if (elect()) {
                        bulk_commit();
                        asm volatile("cp.async.bulk.wait_group 0;" ::: "memory");
                        mbar_arrive(bars + B_TF);
                        fence_async_gmem();
                        red_release(p.sync + SY_R);
                        PROF(22);
                    }
                } else {
                    warp_arrive(bars + B_TF);
                }
            } else {
                if (lane == 0) prefetch_map(&tmO);
                mbar_wait(bars + B_XF, 0);
                if (elect()) red_relaxed(p.sync + SY_L);
                wait_count(p.sync + SY_L, epoch1 * NCTA);
                warp_arrive(bars + B_GO);
                if (lane == 0) PROF(42);
                if (cta == 0 && lane < 16) *(volatile uint32_t*)(p.sync + lane * 32) = epoch1;
                mbar_wait(bars + B_TF, 0);
                wait_count(p.sync + SY_R, epoch1 * RCTA);
                fence_async_gmem();
                warp_arrive(bars + B_RGO);
                if (lane == 0) PROF(23);
#pragma unroll 1
                for (int k = 0; k < 7; ++k) {
                    mbar_wait(bars + B_RND + k * 8, 0);
                    fence_async_smem();
                    if (elect()) {
                        const int row = (quarter * UPQ + k * AW) * 16;
                        tma2d_add(&tmO, sb + SM_X + k * (AW * 256), slice * 8, row);
                        if (k < 6 || quarter == 3) tma2d_add(&tmO, sb + SM_X + k * (AW * 256) + 3072, slice * 8, row + 192);
                        bulk_commit();
                    }
                }
                if (lane == 0) PROF(8);
                bulk_wait_read<0>();
                if (lane == 0) PROF(9);
            }
        }
    } else {
        const int g = lane >> 2, t = lane & 3;
        const int wi = warp < GW ? warp + LW : warp - GW;
        const int u0 = quarter * UPQ + wi;
        const int nun = 6 + (wi < nlast);
        Unit x0, x1;
        auto fetch = [&](Unit& x, int k) {
            const int u = u0 + k * AW;
            x.a = LDIDX(p.idx + u * 64 + lane); x.b = LDIDX(p.idx + u * 64 + 32 + lane);
        };
        if (warp < GW) {
            const int wg = warp >> 2, w4 = warp & 3;
            uint32_t h[20];
            if (rowcta) {
#pragma unroll
                for (int j = 0; j < 10; ++j) h[j] = __ldg((const uint32_t*)p.dis + (node0 >> 1) + 4 * j + t);
            }
            bar_sync(0, GT + 128);
            {
                const uint32_t qa = sS + A3 * UNIT + wg * 2048 + (lane & 15) * 128 + (((lane >> 4) ^ (lane & 7)) << 4);
                const uint32_t ka = sS + (A3 + 1) * UNIT + wg * 4096 + (w4 * 8 + (lane & 7)) * 128 + (((lane >> 3) ^ (lane & 7)) << 4);
                mbar_wait(bars + B_QK, 0);
                __syncwarp();
                if (tid == 0) PROF(33);
                const uint4 b0 = ldsm4(ka), b1 = ldsm4(ka ^ 64), a0 = ldsm4(qa), a1 = ldsm4(qa ^ 32), a2 = ldsm4(qa ^ 64), a3 = ldsm4(qa ^ 96);
                float c[4] = {0.f, 0.f, 0.f, 0.f}, e[4] = {0.f, 0.f, 0.f, 0.f};
                mma16816(c, a0.x, a0.y, a0.z, a0.w, b0.x, b0.y); mma16816(e, a1.x, a1.y, a1.z, a1.w, b0.z, b0.w);
                mma16816(c, a2.x, a2.y, a2.z, a2.w, b1.x, b1.y); mma16816(e, a3.x, a3.y, a3.z, a3.w, b1.z, b1.w);
                float* red = (float*)(smem + SM_X);
                *(float2*)(red + (wg * 16 + g) * 32 + (((w4 + g) & 3) * 8) + 2 * t)     = make_float2(c[0] + e[0], c[1] + e[1]);
                *(float2*)(red + (wg * 16 + g + 8) * 32 + (((w4 + g) & 3) * 8) + 2 * t) = make_float2(c[2] + e[2], c[3] + e[3]);
                bar_sync(1, GT);
                if (wg == 0) {
                    const float* rp = red + (tid >> 3) * 32 + (((tid & 7) * 4 + (tid & 24)) & 31);
                    const float4 v0 = *(const float4*)rp, v1 = *(const float4*)(rp + 512), v2 = *(const float4*)(rp + 1024), v3 = *(const float4*)(rp + 1536);
                    p.M[(i0 + (tid >> 3)) * 64 + (j0 >> 2) + (tid & 7)] =
                        make_uint2(pack_bf16((v0.x + v1.x) + (v2.x + v3.x), (v0.y + v1.y) + (v2.y + v3.y)),
                                   pack_bf16((v0.z + v1.z) + (v2.z + v3.z), (v0.w + v1.w) + (v2.w + v3.w)));
                    bar_arrive(3, 128 + 32);
                }
            }
            if (rowcta) {
                float d[40];
                const uint32_t uw = sS + wg * UNIT, fb = bars + B_F;
                fence_async_smem();
                if (GSENT) mbar_wait(bars + B_SENT, 0);
                gemm_quarter<0>(d, uw + A0 * UNIT, sT, bars + B_K, 0);
                if (tid == 0) PROF(10);
                gemm_quarter<1>(d, uw + A1 * UNIT, sT, bars + B_K, 0, fb);
                gemm_quarter<2>(d, uw + A2 * UNIT, sT, bars + B_K, 0, fb + 8);
                gemm_quarter<3>(d, uw + A4 * UNIT, sT, bars + B_K, 0, fb + 16);
                wg_wait<0>(); warp_arrive(fb + 24);
                if (tid == 0) PROF(11);
#pragma unroll
                for (int j = 9; j >= 0; --j) {
                    const float s0 = blo(h[j]), s1 = bhi(h[j]);
                    h[2 * j + 1] = pack_bf16(d[4 * j + 2] * s0, d[4 * j + 3] * s1);
                    h[2 * j]     = pack_bf16(d[4 * j] * s0, d[4 * j + 1] * s1);
                }
                mbar_wait(fb + 24, 0);
                __syncwarp();
                {
                    const uint32_t sa = sS + A4 * UNIT + warp * 2560 + (lane & 8) * 160 + (lane >> 4) * 128 + (lane & 7) * 16;
#pragma unroll
                    for (int i = 0; i < 5; ++i) stsm4t(sa + i * 256, h[4 * i], h[4 * i + 1], h[4 * i + 2], h[4 * i + 3]);
                }
                warp_arrive(bars + B_HS);
                gemm_quarter<0>(d, uw + A0 * UNIT, sT, bars + B_K, 1);
                if (tid == 0) PROF(12);
                gemm_quarter<1>(d, uw + A1 * UNIT, sT, bars + B_K, 1, fb + 32);
                gemm_quarter<2>(d, uw + A2 * UNIT, sT, bars + B_K, 1, fb + 40);
                gemm_quarter<3>(d, uw + A0 * UNIT, sT, bars + B_K, 1, fb + 48);
                if (tid == 0) PROF(13);
                wg_wait<0>(); warp_arrive(fb + 56);
                if (tid == 0) PROF(14);
                pack_acc(h, d);
                mbar_wait(fb + 56, 0);
                __syncwarp();
                store_tile(h, sT, wg, w4, lane);
                warp_arrive(bars + B_Q);
                mbar_wait(bars + B_LF, 0);
                const bool fast = !lds32(bars + MI_EBAD);
                const uint32_t rows = uw + (w4 & 1) * 4096 + (lane & 4) * 512 + (lane & 8) * 64 + (((lane ^ (lane >> 2 & 4)) & 7) << 4);
#pragma unroll 1
                for (int c = w4 >> 1; c < 4; c += 2) {
                    const int n = 16 * wg + 4 * c + 2 * (w4 & 1);
                    if (stage) mbar_wait(bars + B_A + (4 * wg + c) * 8, 0);
                    if (tid == 0) PROF(c ? 50 : 15);
                    if (tid == 96) PROF(c == 1 ? 51 : 52);
                    if (fast) {
                        const uint32_t ra = rows + (A_TILES >> (8 * c) & 255) * UNIT;
                        uint4 r[2][4];
#pragma unroll
                        for (int kb = 0; kb < 4; ++kb) { r[0][kb] = ldsm4(ra + kb * 128); r[1][kb] = ldsm4(ra + 1024 + kb * 128); }
                        warp_arrive(bars + B_FA + c * 8);
                        if (c < 2) mbar_wait(bars + B_Q, 0);
                        __syncwarp();
                        attention_frags(r, sT, n, lane);
                    } else {
                        warp_arrive(bars + B_FA + c * 8);
                        mbar_wait(bars + B_Q, 0);
                        attention_generic(p, sT, n, node0 + n, lane); attention_generic(p, sT, n + 1, node0 + n + 1, lane);
                    }
                }
                fence_async_smem();
                warp_arrive(bars + B_Z);
                if (tid == 0) PROF(16);
                mbar_wait(bars + B_Z, 0);
                if (tid == 0) PROF(17);
                gemm_quarter<0>(d, uw + A3 * UNIT, sT, bars + B_K, 0);
                gemm_quarter<1>(d, uw + A1 * UNIT, sT, bars + B_K, 0, fb + 64);
                gemm_quarter<2>(d, uw + A2 * UNIT, sT, bars + B_K, 0, fb + 72);
                const bool early = EFETCH && mbar_test(bars + B_GO, 0);
                if (early) { fetch(x0, 0); fetch(x1, 1); }
                gemm_quarter<3>(d, uw + A5 * UNIT, sT, bars + B_K, 0, fb + 80);
                wg_wait<0>(); warp_arrive(fb + 88);
                if (tid == 0) PROF(18);
                pack_acc(h, d);
                mbar_wait(fb + 88, 0);
                __syncwarp();
                store_tile(h, sT, wg, w4, lane);
                warp_arrive(bars + B_R);
                if (!early) { mbar_wait(bars + B_GO, 0); fetch(x0, 0); fetch(x1, 1); }
                if (tid == 0) PROF(19);
            } else {
                mbar_wait(bars + B_GO, 0);
                fetch(x0, 0); fetch(x1, 1);
            }
        } else {
            const int lw = warp - GW, tl = tid - GT;
            const uint32_t epoch = ld_relaxed(p.sync + (cta & 15) * 32);
            uint32_t dd[5], ss[5];
            {
                const int e0 = cta * p.chunk, e1 = min(e0 + p.chunk, p.Efast);
#pragma unroll
                for (int k = 0; k < 5; ++k) { dd[k] = (RCTA + (lane & 1)) * NPC; ss[k] = 0; }
#pragma unroll
                for (int k = 0; k < 2; ++k) {
                    const int e = e0 + 2 * (tl + k * LT);
                    if (e < e1) {
                        const int2 d = __ldg((const int2*)(p.dst + e)), s = __ldg((const int2*)(p.src + e));
                        dd[2 * k] = d.x; dd[2 * k + 1] = d.y; ss[2 * k] = s.x; ss[2 * k + 1] = s.y;
                    }
                }
                const int e = e0 + 4 * LT + tl;
                if (e < e1) { dd[4] = __ldg(p.dst + e); ss[4] = __ldg(p.src + e); }
            }
            int4 ed = make_int4(0, 0, 0, 0), es = make_int4(0, 0, 0, 0);
            if (stage) {
                if (tl < NPC) ed = __ldg((const int4*)p.edst + node0 + tl);
                es = __ldg((const int4*)p.esrc + node0 + 64 + 2 * lw + (lane >> 4));
            }
            const uint32_t oba = sb + X_OUT + (tl ^ ((tl >> 3) & 7)) * 16;
#pragma unroll
            for (int r = 0; r < 4; ++r) { const uint32_t e = (NPC * 8 + (cta & 3) * 8 + (tl & 7)) << 17; sts128(oba + r * LT * 16, make_uint4(e, e, e, e)); }
            if (tl < 32) sts128(bars + MI_PCNT + tl * 16, make_uint4(0, 0, 0, 0));
            if (tl == 32) { sts32(bars + MI_SLOW, p.force_slow); sts32(bars + MI_EBAD, p.force_eslow); sts32(bars + MI_NOVF, 0); sts32(bars + MI_FLAGS, 0); }
            bar_sync(2, LT);
            if (tl == 0) PROF(34);
            const int zero = lds32(bars + MI_PCNT + 127 * 4);
            {
                uint32_t q[5], c[5], qm = 0;
#pragma unroll
                for (int k = 0; k < 5; ++k) {
                    dd[k] += zero;
                    c[k] = dd[k] / NPC;
                    q[k] = atoms_add(bars + MI_PCNT + c[k] * 4, c[k] < RCTA);
                }
                if (tl == 0) PROF(36);
#pragma unroll
                for (int k = 0; k < 5; ++k) {
                    const uint32_t w = (((dd[k] - c[k] * NPC) * 8 + (ss[k] & 7u)) << 17) + ss[k] + (W_VALID + 8);
                    sts32(sb + X_OUT + c[k] * 128 + (((q[k] ^ c[k] ^ ((q[k] >> 4) * 7)) & 7u) << 4) + ((q[k] >> 1) & 12u), w);
                    qm |= q[k];
                }
                const int nz = node0 + tl + zero;
                const bool ebad = stage && tl < NPC && ((ed.x != nz) | (ed.y != nz) | (ed.z != nz) | (ed.w != nz));
                const uint32_t fl = (ebad ? W_EBAD : 0u) | (qm > 31 ? W_OVF : 0u);
                if (fl) asm volatile("red.shared.or.b32 [%0], %1;" :: "r"(bars + MI_FLAGS), "r"(fl) : "memory");
            }
            if (tl == 0) PROF(37);
            bar_sync(4, LT + 128);
            if (tl == 0) PROF(24);
            const uint32_t tag = ((epoch + zero) % 31u + 1u) << 27;
            {
                const uint32_t fl = lds32(bars + MI_FLAGS) | tag;
                uint4* const gp = p.cells + ((tl >> 3) * NCTA + cta) * 8 + (tl & 7);
#pragma unroll
                for (int r = 0; r < 4; ++r) {
                    uint4 w = lds128(oba + r * LT * 16);
                    w.x |= fl; w.y |= tag; w.z |= tag; w.w |= tag;
                    if (r < 3 || tl + r * LT < RCTA * 8) gp[r * (LT / 8) * NCTA * 8] = w;
                }
            }
            warp_arrive(bars + B_SENT);
            if (tl == 0) { sts32(bars + MI_EPOCH, epoch); mbar_arrive(bars + B_EPO); }
            if (tl == 0) PROF(25);
            uint4 r[4][2];
            auto load_rows = [&]() {
                if (stage) {
                    const char* xl = p.x + (lane & 15) * 16;
                    const char* r0 = row_ptr(xl, es.x); const char* r1 = row_ptr(xl, es.y); const char* r2 = row_ptr(xl, es.z); const char* r3 = row_ptr(xl, es.w);
                    r[0][0] = ldg_in(r0); r[0][1] = ldg_in(r0 + 256); r[1][0] = ldg_in(r1); r[1][1] = ldg_in(r1 + 256);
                    r[2][0] = ldg_in(r2); r[2][1] = ldg_in(r2 + 256); r[3][0] = ldg_in(r3); r[3][1] = ldg_in(r3 + 256);
                }
            };
            if (rowcta) {
                bar_sync(2, LT);
                sts128(sb + X_IMG + tl * 16, make_uint4(0, 0, 0, 0));
                if (tl < (X_TAB - X_IMG) / 16 - LT) sts128(sb + X_IMG + (LT + tl) * 16, make_uint4(0, 0, 0, 0));
                if (tl >= LT - 16) sts128(sb + X_RU - (LT - tl) * 16, make_uint4(64, 64, 64, 64));
                bar_sync(2, LT);
                uint4 cw[4];
                const uint4* cp = p.cells + cta * (NCTA * 8) + tl;
                mbar_wait(bars + B_CGO, 0);
                uint32_t pend = 15u;
#pragma unroll 1
                for (int it = 0; it < SPIN_LIMIT && pend; ++it) {
#pragma unroll
                    for (int m = 0; m < 4; ++m) if (pend >> m & 1u) cw[m] = ld_relaxed4(cp + m * LT);
#pragma unroll
                    for (int m = 0; m < 4; ++m)
                        if (__all_sync(0xffffffffu, (((cw[m].x ^ tag) | (cw[m].y ^ tag) | (cw[m].z ^ tag) | (cw[m].w ^ tag)) >> 27) == 0)) pend &= ~(1u << m);
                }
                const uint32_t st = cw[0].x | cw[1].x | cw[2].x | cw[3].x;
                if (tl == 0 && st != 77) PROF(26);
                if (st & W_OVF)  sts32(bars + MI_SLOW, 1);
                if (st & W_EBAD) sts32(bars + MI_EBAD, 1);
                const uint32_t none = (NPC * 8 + lane) << 17;
                auto lose = [&](uint32_t (&w)[8], uint32_t (&key)[8], uint32_t bits) {
                    uint32_t any = 0;
#pragma unroll
                    for (int m = 0; m < 8; ++m) any |= key[m];
                    if (__any_sync(0xffffffffu, any & bits)) {
#pragma unroll 1
                        for (int n = 0; n < 8; ++n) {
                            uint32_t v = 0;
#pragma unroll
                            for (int m = 0; m < 8; ++m)
                                if (!v && (key[m] & bits)) { v = w[m]; key[m] = 0; w[m] = none; }
                            if (!__any_sync(0xffffffffu, v)) break;
                            if (v) { const uint32_t o = atoms_add(bars + MI_NOVF, 1); sts32(bars + (o < OVCAP ? MI_OVF + o * 4 : MI_SLOW), v & W_KEEP); }
                        }
                    }
                };
                if (__any_sync(0xffffffffu, (cw[0].z | cw[1].z | cw[2].z | cw[3].z) & W_VALID)) {
#pragma unroll
                    for (int m = 0; m < 4; ++m)
                        if (!(cw[m ^ 1].y & W_VALID)) { cw[m ^ 1].y = cw[m].z; cw[m].z = none; }
                    uint32_t z[8] = {cw[0].z, cw[0].w, cw[1].z, cw[1].w, cw[2].z, cw[2].w, cw[3].z, cw[3].w};
                    lose(z, z, W_VALID);
                }
                uint32_t w[8] = {cw[0].x, cw[0].y, cw[1].x, cw[1].y, cw[2].x, cw[2].y, cw[3].x, cw[3].y};
                {
                    uint32_t c[8];
#pragma unroll
                    for (int m = 0; m < 8; ++m) {
                        const uint32_t v = (w[m] >> 16) & 1u;
                        w[m] &= W_KEEP;
                        c[m] = atoms_add(sb + X_CNT + (w[m] >> 15), v);
                    }
                    lose(w, c, ~7u);
#pragma unroll
                    for (int m = 0; m < 8; ++m) w[m] += c[m] << 14;
                }
                bar_sync(2, LT);
                if (tl == 0) { mbar_arrive(bars + B_LF); PROF(27); }
                if (lw < 3) {
                    const int dl = min(tl, NPC + 7 - ((NPC + 7 - tl) & 7) - 8);
                    const uint4 n0 = lds128(sb + X_CNT + dl * 32), n1 = lds128(sb + X_CNT + dl * 32 + 16);
                    uint32_t pk = min(n0.x, 8u) + (min(n0.y, 8u) << 4) + (min(n0.z, 8u) << 8) + (min(n0.w, 8u) << 12) +
                                  (min(n1.x, 8u) << 16) + (min(n1.y, 8u) << 20) + (min(n1.z, 8u) << 24) + (min(n1.w, 8u) << 28);
                    pk = __funnelshift_r(pk, pk, 4 * lane);
                    uint32_t du = 0xf0000000u, ru = 0, b6 = 0, b7 = 0, m[7] = {0, 0, 0, 0, 0, 0, 0};
                    auto code2 = [&](uint32_t b0, uint32_t b1) {
                        return __byte_perm(__float_as_uint(__uint_as_float(b0) * 8388608.f), __float_as_uint(__uint_as_float(b1) * 8388608.f), 0x7632);
                    };
                    auto pass_on = [&](int k) {
                        ru = __shfl_sync(0xffffffffu, ru, lane + 1, 8);
                        const uint32_t t0 = (code2(m[0] ^ m[1], m[2] ^ m[3]) >> 7) + code2(m[1] ^ m[2], m[3] ^ m[4]) * 2;
                        const uint32_t t1 = (code2(m[4] ^ m[5], b6) >> 7) + code2(m[5] ^ m[6], b7) * 2;
                        asm volatile("st.shared.v2.u32 [%0], {%1, %2};" :: "r"(sb + X_TAB + dl * 64 + ((lane + k + 7) & 7) * 8), "r"(t0), "r"(t1) : "memory");
                    };
#pragma unroll 1
                    for (int k = 0; k < 8; ++k) {
                        const uint32_t th = ~(~0u << (pk & 15u));
                        const bool big = __any_sync(0xffffffffu, th > 63u);
                        pk >>= 4;
                        pass_on(k);
                        m[0] = ~(du | ru);
#pragma unroll
                        for (int c = 0; c < 6; ++c) m[c + 1] = m[c] & (m[c] - ((th >> c) & 1u));
                        uint32_t ml = m[6];
                        if (big) {
                            const uint32_t m7 = ml & (ml - ((th >> 6) & 1u)), m8 = m7 & (m7 - (th >> 7));
                            b6 = ml ^ m7; b7 = m7 ^ m8;
                            ml = m8;
                        }
                        du |= ml ^ m[0];
                        ru |= ml ^ m[0];
                    }
                    pass_on(8);
                    sts32(sb + X_RU + dl * 4, ru);
                }
                if (tl == 0) PROF(49);
                if (LROW == 0) load_rows();
                bar_sync(2, LT);
                if (tl == 0) PROF(28);
                const int v = LT - 1 - tl;
                if (lw >= 6 && v < 40) {
                    const uint4 b = lds128(sb + X_RU + (v >> 2) * 32), e = lds128(sb + X_RU + (v >> 2) * 32 + 16);
                    const uint32_t f2 = b.x & b.y & b.z & b.w;
                    const uint32_t s0 = (f2 & e.x) | (~f2 & b.x), s1 = (f2 & e.y) | (~f2 & b.y), s2 = (f2 & e.z) | (~f2 & b.z);
                    const uint32_t f1 = s0 & s1, f0 = (f1 & s2) | (~f1 & s0);
                    uint32_t u[4];
#pragma unroll
                    for (int k = 0; k < 4; ++k) {
                        const int sh = (v & 3) * 8 + 2 * k;
                        u[k] = ((((f0 >> sh) & 3u) * 0x8001u) & 0x10001u) + ((((f1 >> sh) & 3u) * 0x10002u) & 0x20002u) + ((((f2 >> sh) & 3u) * 0x20004u) & 0x40004u);
                    }
                    sts128(sb + X_DEF + v * 16, make_uint4(u[0], u[1], u[2], u[3]));
                }
                {
                    uint32_t rd[8];
#pragma unroll
                    for (int m = 0; m < 8; ++m) asm volatile("ld.shared.u8 %0, [%1];" : "=r"(rd[m]) : "r"(sb + X_TAB + (w[m] >> 14)) : "memory");
#pragma unroll
                    for (int m = 0; m < 8; ++m) {
                        rd[m] -= 1;
                        if (rd[m] < 48) sts16(sb + X_IMG + ((w[m] >> 14) & ~63u) + min(rd[m], 31u) * 2, w[m] & 0x3fffu);
                    }
                    lose(w, rd, 0x80000000u);
                }
                if (LROW == 1) load_rows();
                bar_sync(2, LT);
                if (tl == 0) PROF(29);
#pragma unroll 1
                for (int set = lw; set < 10; set += lw >= 3 && lw < 5 ? 5 : 10) publish(set);
            }
            warp_arrive(bars + B_XF);
            if (tl == 0) PROF(30);
            if (rowcta) {
                mbar_wait(bars + B_Q, 0);
                __syncwarp();
                if (!lds32(bars + MI_EBAD)) attention_chunks(r, sT, 64 + 2 * lw, lane);
                else { attention_generic(p, sT, 64 + 2 * lw, node0 + 64 + 2 * lw, lane); attention_generic(p, sT, 65 + 2 * lw, node0 + 65 + 2 * lw, lane); }
                fence_async_smem();
                warp_arrive(bars + B_Z);
                if (tl == 0) PROF(32);
            }
            mbar_wait(bars + B_GO, 0);
            fetch(x0, 0); fetch(x1, 1);
        }
        const uint32_t dsel = (g >> 1) == t ? (g & 1 ? 0x3244u : 0x4432u) : 0x4444u;
        const uint32_t stg = sb + SM_X + wi * 256 + (lane & 15) * 16;
        const uint32_t lt = list_tag(lds32(bars + MI_EPOCH)), base = sS - (lt & 0xffffu) * 16;
        auto pair = [&](Unit& c0, Unit& c1, Unit& n0, Unit& n1, int k) {
#pragma unroll 1
            for (int it = 0; it < SPIN_LIMIT && __any_sync(0xffffffffu, unit_stale(c0, lt) | unit_stale(c1, lt)); ++it) { fetch(c0, k); fetch(c1, min(k + 1, nun - 1)); }
            if (k + 2 < nun) { fetch(n0, k + 2); if (k + 3 < nun) fetch(n1, k + 3); }
            agg_unit(c0, base, dsel, stg + k * (AW * 256), lt);
            warp_arrive(bars + B_RND + k * 8);
            if (k + 1 < nun) {
                agg_unit(c1, base, dsel, stg + (k + 1) * (AW * 256), lt);
                warp_arrive(bars + B_RND + k * 8 + 8);
            }
        };
        Unit y0, y1;
        mbar_wait(bars + B_S, 0);
        __syncwarp();
        if (tid == 0) PROF(20);
#pragma unroll 1
        for (int k = 0; k < 8; k += 4) {
            if (k) { mbar_wait(bars + B_TF, 0); __syncwarp(); }
            pair(x0, x1, y0, y1, k);
            if (k + 2 < nun) pair(y0, y1, x0, x1, k + 2);
        }
        if (tid == 0) PROF(21);
        const bool slow = rowcta && lds32(bars + MI_SLOW);
        const int novf = lds32(bars + MI_NOVF);
        if (slow || AW - 1 - wi < novf) {
            mbar_wait(bars + B_RGO, 0);
            if (slow) local_generic(p, node0, wi, lane);
            else {
#pragma unroll 1
                for (int o = AW - 1 - wi; o < novf; o += AW) {
                    const uint32_t w = lds32(bars + MI_OVF + o * 4);
                    const int n = node0 + (w >> 20);
                    float a[8] = {0.f, 0.f, 0.f, 0.f, 0.f, 0.f, 0.f, 0.f};
                    fma8(a, 1.f, ldg_sc(p.H + lane * N + (w & 0x3fffu) - 8));
                    red_row(p.out + n * 32 + lane, pack8(a, __bfloat162float(p.dis[n])));
                }
            }
        }
    }
    PROF_FLUSH();
}

typedef CUresult (*EncodeFn)(CUtensorMap*, CUtensorMapDataType, cuuint32_t, void*, const cuuint64_t*, const cuuint64_t*,
                             const cuuint32_t*, const cuuint32_t*, CUtensorMapInterleave, CUtensorMapSwizzle,
                             CUtensorMapL2promotion, CUtensorMapFloatOOBfill);

static void make_map(EncodeFn enc, CUtensorMap* m, const void* ptr, int rows, int box_cols, int box_rows) {
    cuuint64_t dims[2] = {(cuuint64_t)D, (cuuint64_t)rows};
    cuuint64_t strides[1] = {(cuuint64_t)D * 2};
    cuuint32_t box[2] = {(cuuint32_t)box_cols, (cuuint32_t)box_rows};
    cuuint32_t es[2] = {1u, 1u};
    enc(m, CU_TENSOR_MAP_DATA_TYPE_BFLOAT16, 2, const_cast<void*>(ptr), dims, strides, box, es, CU_TENSOR_MAP_INTERLEAVE_NONE,
        box_cols == 64 ? CU_TENSOR_MAP_SWIZZLE_128B : CU_TENSOR_MAP_SWIZZLE_NONE,
        box_cols == 64 ? PROMO : CU_TENSOR_MAP_L2_PROMOTION_NONE, CU_TENSOR_MAP_FLOAT_OOB_FILL_NONE);
}
static void make_map3(EncodeFn enc, CUtensorMap* m, const void* ptr, int rows, int box_rows) {
    cuuint64_t dims[3] = {64, (cuuint64_t)rows, 4};
    cuuint64_t strides[2] = {(cuuint64_t)D * 2, 128};
    cuuint32_t box[3] = {64u, (cuuint32_t)box_rows, 4u};
    cuuint32_t es[3] = {1u, 1u, 1u};
    enc(m, CU_TENSOR_MAP_DATA_TYPE_BFLOAT16, 3, const_cast<void*>(ptr), dims, strides, box, es, CU_TENSOR_MAP_INTERLEAVE_NONE,
        CU_TENSOR_MAP_SWIZZLE_128B, CU_TENSOR_MAP_L2_PROMOTION_L2_256B, CU_TENSOR_MAP_FLOAT_OOB_FILL_NONE);
}

}

extern "C" void kernel_launch(void* const* d_in, const int* in_sizes, int n_in, void* d_out, int out_size) {
    using namespace gk;
    (void)n_in; (void)out_size;
    static EncodeFn enc = nullptr;
    static void *m_ptr, *cells_ptr, *sync_ptr, *h_ptr, *idx_ptr;
    if (!enc) {
        void* fn = nullptr;
        cudaDriverEntryPointQueryResult qr;
        cudaGetDriverEntryPoint("cuTensorMapEncodeTiled", &fn, cudaEnableDefault, &qr);
        enc = (EncodeFn)fn;
        cudaGetSymbolAddress(&m_ptr, g_M);
        cudaGetSymbolAddress(&cells_ptr, g_cells);
        cudaGetSymbolAddress(&sync_ptr, g_sync);
        cudaGetSymbolAddress(&h_ptr, g_H);
        cudaGetSymbolAddress(&idx_ptr, g_idx);
        cudaFuncSetAttribute(fused_kernel, cudaFuncAttributeMaxDynamicSharedMemorySize, SM_ALLOC);
    }
    if (in_sizes[5] != N || in_sizes[0] != N * D) return;
    Params p;
    p.src  = (const int*)d_in[1];
    p.dst  = (const int*)d_in[2];
    p.esrc = (const int*)d_in[3];
    p.edst = (const int*)d_in[4];
    p.sync = (uint32_t*)sync_ptr;
    p.x    = (const char*)d_in[0];
    p.dis  = (const __nv_bfloat16*)d_in[5];
    p.cells = (uint4*)cells_ptr;
    p.H    = (uint4*)h_ptr;
    p.idx  = (uint4*)idx_ptr;
    p.M    = (uint2*)m_ptr;
    p.out  = (uint4*)d_out;
    p.E  = in_sizes[1];
    p.Ee = in_sizes[3];
    p.chunk = (((p.E + NCTA - 1) / NCTA) + 1) & ~1;
    p.force_slow  = (p.chunk > 5 * LT || (p.E & 1)) ? 1 : 0;
    p.force_eslow = (p.Ee != 4 * N) ? 1 : 0;
    p.Efast = p.force_slow ? 0 : p.E;

    CUtensorMap tmX, tmWl, tmM, tmWv, tmR, tmO, tmG, tmQ, tmK;
    make_map(enc, &tmX, d_in[0], N, 64, NPC);
    make_map3(enc, &tmWl, d_in[6], D, 64);
    make_map3(enc, &tmM, m_ptr, D, 64);
    make_map3(enc, &tmWv, d_in[9], D, 64);
    make_map(enc, &tmR, d_out, N, 64, 16);
    make_map(enc, &tmO, d_out, N, 8, 192);
    make_map(enc, &tmG, d_in[0], N, 256, 1);
    make_map3(enc, &tmQ, d_in[7], D, 16);
    make_map3(enc, &tmK, d_in[8], D, 32);
    fused_kernel<<<NCTA, NTHR, SM_ALLOC, cudaStreamPerThread>>>(p, tmX, tmWl, tmM, tmWv, tmR, tmO, tmG, tmQ, tmK);
}
```

```cpp
#include <cuda_runtime.h>
#include <cuda_bf16.h>
#include <cuda.h>
#include <stdint.h>

#define PROFILE 0

namespace gk {

constexpr int N      = 10000;
constexpr int D      = 256;
constexpr int NPC    = 80;
constexpr int NCTA   = 128;
constexpr int RCTA   = N / NPC;
constexpr int NSET   = N / 8;
constexpr int GW     = 16;
constexpr int LW     = 8;
constexpr int AW     = GW + LW;
constexpr int GT     = GW * 32, LT = LW * 32;
constexpr int NTHR   = (AW + 4) * 32;
constexpr int UPQ    = 156;
constexpr int OVCAP  = 64;
#define SPINB 18
constexpr int SPIN_LIMIT = 1 << SPINB;

constexpr int KB      = NPC * 128;
constexpr int UNIT    = 8192;
constexpr int SM_S    = 0;
constexpr int SM_X    = 20 * UNIT;
constexpr int SM_T    = 23 * UNIT;
constexpr int SM_MISC = SM_T + 4 * KB;
constexpr int SM_END  = SM_MISC + 2464;
constexpr int SLICE_END = 128 + N * 16;
constexpr int X_OUT  = SM_X + UNIT;
constexpr int X_IMG  = X_OUT;
constexpr int X_CNT  = X_IMG + NPC * 64;
constexpr int X_TAB  = X_CNT + NPC * 32 + 128;
constexpr int X_RU   = X_TAB + NPC * 64 + 16;
constexpr int X_DEF  = X_RU + NPC * 4;
constexpr int X_ZERO = X_OUT + 2 * UNIT - 2048;
static_assert(X_DEF + 640 <= X_ZERO, "list scratch");
constexpr int B_K = 0, B_QK = 32, B_EPO = 40,
              B_A = 48,
              B_F = 176, B_HS = 272, B_Q = 280, B_R = 288,
              B_GO = 296, B_LF = 304, B_TF = 312, B_RGO = 320, B_CGO = 328, B_MI = 336, B_HR = 344,
              B_Z = 352,
              B_FA = 360, B_XF = 392, B_SENT = 400, B_S = 408, B_VE = 416,
              B_RND = 424;
constexpr int MI_EPOCH = 528, MI_EBAD = 532, MI_SLOW = 536, MI_NOVF = 540, MI_FLAGS = 544;
constexpr int MI_OVF  = 1280;
constexpr int MI_ES   = 768;
constexpr int MI_PCNT = 1792;
constexpr int MI_DIS  = 2304;
constexpr int A0 = 0, A1 = 4, A2 = 8, A3 = 12, A4 = 16, A5 = 19;
constexpr uint32_t A_TILES = A3 | A1 << 8 | A2 << 16 | A0 << 24;
#define PROMO CU_TENSOR_MAP_L2_PROMOTION_L2_128B
#define GSENT 1
#define EFETCH 1
#define VPF 1
#define RPER 0
#define ER 2
#define G3 1
#define HGATE 0
#define CHK1 0
#define HPER 160
#define HRW 1
#define T0BAR B_CGO
#define LROW 0

constexpr uint32_t W_OVF = 1u << 14, W_EBAD = 1u << 15, W_VALID = 1u << 16, W_KEEP = 0x07fe3fffu;

__device__ uint4         g_cells[RCTA * NCTA * 8];
__device__ uint4         g_H[32 * N];
__device__ uint4         g_idx[NSET * 32];
__device__ __nv_bfloat16 g_M[D * D];
__device__ uint32_t      g_sync[20 * 32];
constexpr int SY_M = 16 * 32, SY_H = 17 * 32, SY_L = 18 * 32, SY_R = 19 * 32;
#define PROF(i) do {} while (0)
#define PROF_FLUSH() do {} while (0)
constexpr int SM_ALLOC = SM_END;
static_assert(SM_ALLOC <= 232448, "shared memory");

struct Params {
    const int* src; const int* dst;
    uint32_t* sync;
    const int* esrc; const int* edst;
    int Efast, chunk;
    const __nv_bfloat16* dis;
    const char* x; const char* wv;
    uint4* cells; uint2* M;
    int force_slow, force_eslow;
    uint4* idx; uint4* H; uint4* out;
    int E, Ee;
};

__device__ __forceinline__ uint32_t s32(const void* p) { return (uint32_t)__cvta_generic_to_shared(p); }
__device__ __forceinline__ void mbar_init(uint32_t a, uint32_t cnt) { asm volatile("mbarrier.init.shared.b64 [%0], %1;" :: "r"(a), "r"(cnt) : "memory"); }
__device__ __forceinline__ void mbar_arrive(uint32_t a) { asm volatile("mbarrier.arrive.shared.b64 _, [%0];" :: "r"(a) : "memory"); }
__device__ __forceinline__ void mbar_expect(uint32_t a, uint32_t bytes) { asm volatile("mbarrier.arrive.expect_tx.shared.b64 _, [%0], %1;" :: "r"(a), "r"(bytes) : "memory"); }
__device__ __forceinline__ void mbar_wait(uint32_t a, uint32_t parity) {
    uint32_t ok = 0;
#pragma unroll 1
    for (int it = 0; it < SPIN_LIMIT && !ok; ++it)
        asm volatile("{\n.reg .pred p;\nmbarrier.try_wait.parity.shared.b64 p, [%1], %2;\nselp.u32 %0, 1, 0, p;\n}"
                     : "=r"(ok) : "r"(a), "r"(parity) : "memory");
}
__device__ __forceinline__ bool elect() { uint32_t r; asm volatile("{\n.reg .pred p;\nelect.sync _|p, 0xffffffff;\nselp.u32 %0, 1, 0, p;\n}" : "=r"(r) :: "memory"); return r; }
__device__ __forceinline__ void warp_arrive(uint32_t a) {
    asm volatile("{\n.reg .pred p;\nelect.sync _|p, 0xffffffff;\n@p mbarrier.arrive.shared.b64 _, [%0];\n}" :: "r"(a) : "memory");
}
__device__ __forceinline__ void bar_sync(int id, int n)   { __syncwarp(); asm volatile("bar.sync %0, %1;"   :: "r"(id), "r"(n) : "memory"); }
__device__ __forceinline__ void bar_arrive(int id, int n) { __syncwarp(); asm volatile("bar.arrive %0, %1;" :: "r"(id), "r"(n) : "memory"); }
__device__ __forceinline__ void fence_async_smem() { asm volatile("fence.proxy.async.shared::cta;" ::: "memory"); }
__device__ __forceinline__ void fence_async_gmem() { asm volatile("fence.proxy.async.global;" ::: "memory"); }
__device__ __forceinline__ void tma2d(uint32_t dst, const CUtensorMap* tm, int c0, int c1, uint32_t bar) {
    asm volatile("cp.async.bulk.tensor.2d.shared::cluster.global.mbarrier::complete_tx::bytes [%0], [%1, {%3, %4}], [%2];"
                 :: "r"(dst), "l"(tm), "r"(bar), "r"(c0), "r"(c1) : "memory");
}
__device__ __forceinline__ void tma3d(uint32_t dst, const CUtensorMap* tm, int row, uint32_t bar) {
    asm volatile("cp.async.bulk.tensor.3d.shared::cluster.global.mbarrier::complete_tx::bytes [%0], [%1, {%4, %3, %4}], [%2];"
                 :: "r"(dst), "l"(tm), "r"(bar), "r"(row), "r"(0) : "memory");
}
__device__ __forceinline__ void tma2d_store(const CUtensorMap* tm, uint32_t src, int c0, int c1) {
    asm volatile("cp.async.bulk.tensor.2d.global.shared::cta.bulk_group [%0, {%2, %3}], [%1];"
                 :: "l"(tm), "r"(src), "r"(c0), "r"(c1) : "memory");
}
__device__ __forceinline__ void tma2d_add(const CUtensorMap* tm, uint32_t src, int c0, int c1) {
    asm volatile("cp.reduce.async.bulk.tensor.2d.global.shared::cta.add.bulk_group [%0, {%2, %3}], [%1];"
                 :: "l"(tm), "r"(src), "r"(c0), "r"(c1) : "memory");
}
__device__ __forceinline__ void bulk_load(uint32_t dst, const void* src, uint32_t bytes, uint32_t bar) {
    asm volatile("cp.async.bulk.shared::cluster.global.mbarrier::complete_tx::bytes [%0], [%1], %2, [%3];"
                 :: "r"(dst), "l"(src), "r"(bytes), "r"(bar) : "memory");
}
__device__ __forceinline__ void bulk_store(void* dst, uint32_t src, uint32_t bytes) {
    asm volatile("cp.async.bulk.global.shared::cta.bulk_group [%0], [%1], %2;" :: "l"(dst), "r"(src), "r"(bytes) : "memory");
}
__device__ __forceinline__ uint32_t clk() { uint32_t c; asm volatile("mov.u32 %0, %%clock;" : "=r"(c) :: "memory"); return c; }
__device__ __forceinline__ void wait_clk(uint32_t t) { while ((int)(clk() - t) < 0) {} }
__device__ __forceinline__ void bulk_commit() { asm volatile("cp.async.bulk.commit_group;" ::: "memory"); }
template <int K> __device__ __forceinline__ void bulk_wait_read() { asm volatile("cp.async.bulk.wait_group.read %0;" :: "n"(K) : "memory"); }
__device__ __forceinline__ void prefetch_map(const CUtensorMap* tm) { asm volatile("prefetch.tensormap [%0];" :: "l"(tm) : "memory"); }
__device__ __forceinline__ uint4 lds128(uint32_t a) { uint4 v; asm volatile("ld.shared.v4.u32 {%0,%1,%2,%3}, [%4];" : "=r"(v.x), "=r"(v.y), "=r"(v.z), "=r"(v.w) : "r"(a) : "memory"); return v; }
__device__ __forceinline__ void sts128(uint32_t a, uint4 v) { asm volatile("st.shared.v4.u32 [%0], {%1,%2,%3,%4};" :: "r"(a), "r"(v.x), "r"(v.y), "r"(v.z), "r"(v.w) : "memory"); }
__device__ __forceinline__ uint32_t lds32(uint32_t a) { uint32_t v; asm volatile("ld.shared.u32 %0, [%1];" : "=r"(v) : "r"(a) : "memory"); return v; }
__device__ __forceinline__ void sts32(uint32_t a, uint32_t v) { asm volatile("st.shared.u32 [%0], %1;" :: "r"(a), "r"(v) : "memory"); }
__device__ __forceinline__ void sts16(uint32_t a, uint32_t v) { asm volatile("st.shared.u16 [%0], %1;" :: "r"(a), "h"((unsigned short)v) : "memory"); }
__device__ __forceinline__ uint32_t atoms_add(uint32_t a, uint32_t x) { uint32_t v; asm volatile("atom.shared.add.u32 %0, [%1], %2;" : "=r"(v) : "r"(a), "r"(x) : "memory"); return v; }
__device__ __forceinline__ uint32_t ld_relaxed(const uint32_t* p) { uint32_t v; asm volatile("ld.relaxed.gpu.global.u32 %0, [%1];" : "=r"(v) : "l"(p) : "memory"); return v; }
__device__ __forceinline__ uint4 ld_relaxed4(const uint4* p) { uint4 v; asm volatile("ld.relaxed.gpu.global.L1::no_allocate.v4.u32 {%0,%1,%2,%3}, [%4];" : "=r"(v.x), "=r"(v.y), "=r"(v.z), "=r"(v.w) : "l"(p) : "memory"); return v; }
__device__ __forceinline__ uint32_t ld_acquire(const uint32_t* p) { uint32_t v; asm volatile("ld.acquire.gpu.global.u32 %0, [%1];" : "=r"(v) : "l"(p) : "memory"); return v; }
__device__ __forceinline__ void st_relaxed(uint32_t* p, uint32_t v) { asm volatile("st.relaxed.gpu.global.u32 [%0], %1;" :: "l"(p), "r"(v) : "memory"); }
__device__ __forceinline__ void red_relaxed(uint32_t* p) { asm volatile("red.relaxed.gpu.global.add.u32 [%0], 1;" :: "l"(p) : "memory"); }
__device__ __forceinline__ uint32_t list_tag(uint32_t epoch) { return (epoch % 3u + 1u) * 0x40004000u; }
__device__ __forceinline__ void red_release(uint32_t* p) { asm volatile("red.release.gpu.global.add.u32 [%0], 1;" :: "l"(p) : "memory"); }
__device__ __forceinline__ void wait_count(const uint32_t* p, uint32_t target) {
#pragma unroll 1
    for (int it = 0; it < SPIN_LIMIT; ++it)
        if ((int)(ld_acquire(p) - target) >= 0) break;
}
__device__ __forceinline__ bool mbar_test(uint32_t a, uint32_t parity) {
    uint32_t ok;
    asm volatile("{\n.reg .pred p;\nmbarrier.test_wait.parity.shared.b64 p, [%1], %2;\nselp.u32 %0, 1, 0, p;\n}" : "=r"(ok) : "r"(a), "r"(parity) : "memory");
    return __all_sync(0xffffffffu, ok);
}
__device__ __forceinline__ uint4 ldg_in(const void* p) { uint4 v; asm volatile("ld.global.nc.L1::no_allocate.v4.u32 {%0,%1,%2,%3}, [%4];" : "=r"(v.x), "=r"(v.y), "=r"(v.z), "=r"(v.w) : "l"(p)); return v; }
__device__ __forceinline__ uint4 ldg_sc(const void* p) { uint4 v; asm volatile("ld.global.L1::no_allocate.v4.u32 {%0,%1,%2,%3}, [%4];" : "=r"(v.x), "=r"(v.y), "=r"(v.z), "=r"(v.w) : "l"(p) : "memory"); return v; }
__device__ __forceinline__ void red_row(uint4* p, uint4 v) { asm volatile("red.relaxed.gpu.global.add.noftz.v4.bf16x2 [%0], {%1,%2,%3,%4};" :: "l"(p), "r"(v.x), "r"(v.y), "r"(v.z), "r"(v.w) : "memory"); }
__device__ __forceinline__ uint32_t pack_bf16(float lo, float hi) { uint32_t r; asm("cvt.rn.bf16x2.f32 %0, %1, %2;" : "=r"(r) : "f"(hi), "f"(lo)); return r; }
__device__ __forceinline__ float blo(uint32_t v) { return __uint_as_float(v << 16); }
__device__ __forceinline__ float bhi(uint32_t v) { return __uint_as_float(v & 0xffff0000u); }
__device__ __forceinline__ const char* row_ptr(const char* base, uint32_t row) {
    uint64_t r; asm("mad.wide.u32 %0, %1, 512, %2;" : "=l"(r) : "r"(row), "l"((uint64_t)base)); return (const char*)r;
}

constexpr uint32_t DESC_HI = 64u | (1u << 30);
__device__ __forceinline__ uint32_t desc_lo(uint32_t addr) { return ((addr & 0x3FFFF) >> 4) | (1u << 16); }
__device__ __forceinline__ void wg_fence()  { asm volatile("wgmma.fence.sync.aligned;" ::: "memory"); }
__device__ __forceinline__ void wg_commit() { asm volatile("wgmma.commit_group.sync.aligned;" ::: "memory"); }
template <int K> __device__ __forceinline__ void wg_wait() { asm volatile("wgmma.wait_group.sync.aligned %0;" :: "n"(K) : "memory"); }
#define GK_ACC(c) c(d[0]), c(d[1]), c(d[2]), c(d[3]), c(d[4]), c(d[5]), c(d[6]), c(d[7]), c(d[8]), c(d[9]), \
    c(d[10]), c(d[11]), c(d[12]), c(d[13]), c(d[14]), c(d[15]), c(d[16]), c(d[17]), c(d[18]), c(d[19]), \
    c(d[20]), c(d[21]), c(d[22]), c(d[23]), c(d[24]), c(d[25]), c(d[26]), c(d[27]), c(d[28]), c(d[29]), \
    c(d[30]), c(d[31]), c(d[32]), c(d[33]), c(d[34]), c(d[35]), c(d[36]), c(d[37]), c(d[38]), c(d[39])
#define GK_WGMMA(P) "{\n.reg .pred p;\n.reg .b64 da, db;\nsetp.ne.b32 p, " P ", 0;\nmov.b64 da, {%40, %42};\nmov.b64 db, {%41, %42};\n" \
    "wgmma.mma_async.sync.aligned.m64n80k16.f32.bf16.bf16 " \
    "{%0,%1,%2,%3,%4,%5,%6,%7,%8,%9,%10,%11,%12,%13,%14,%15,%16,%17,%18,%19," \
    "%20,%21,%22,%23,%24,%25,%26,%27,%28,%29,%30,%31,%32,%33,%34,%35,%36,%37,%38,%39}, da, db, p, 1, 1, 1, 0;\n}\n"
template <bool FIRST>
__device__ __forceinline__ void wgmma80(float (&d)[40], uint32_t alo, uint32_t blo_) {
    if (FIRST) asm volatile(GK_WGMMA("0") : GK_ACC("=f") : "r"(alo), "r"(blo_), "r"(DESC_HI));
    else       asm volatile(GK_WGMMA("1") : GK_ACC("+f") : "r"(alo), "r"(blo_), "r"(DESC_HI));
}
template <int KQ>
__device__ __forceinline__ void gemm_quarter(float (&d)[40], uint32_t unit, uint32_t tile, uint32_t bar, uint32_t parity, uint32_t rel = 0) {
    mbar_wait(bar + KQ * 8, parity);
    __syncwarp();
    const uint32_t a = desc_lo(unit), b = desc_lo(tile) + ((KQ * KB) >> 4);
    wg_fence();
    wgmma80<KQ == 0>(d, a, b);
    if (KQ) { wg_commit(); wg_wait<1>(); warp_arrive(rel); }
    wgmma80<false>(d, a + 128, b + 2);
    wgmma80<false>(d, a + 256, b + 4);
    wgmma80<false>(d, a + 384, b + 6);
    wg_commit();
}
__device__ __forceinline__ void stsm4t(uint32_t a, uint32_t r0, uint32_t r1, uint32_t r2, uint32_t r3) {
    asm volatile("stmatrix.sync.aligned.m8n8.x4.trans.shared.b16 [%0], {%1,%2,%3,%4};" :: "r"(a), "r"(r0), "r"(r1), "r"(r2), "r"(r3) : "memory");
}
__device__ __forceinline__ void stsm4(uint32_t a, uint32_t r0, uint32_t r1, uint32_t r2, uint32_t r3) {
    asm volatile("stmatrix.sync.aligned.m8n8.x4.shared.b16 [%0], {%1,%2,%3,%4};" :: "r"(a), "r"(r0), "r"(r1), "r"(r2), "r"(r3) : "memory");
}
__device__ __forceinline__ uint4 ldsm4(uint32_t a) {
    uint4 v; asm volatile("ldmatrix.sync.aligned.m8n8.x4.shared.b16 {%0,%1,%2,%3}, [%4];" : "=r"(v.x), "=r"(v.y), "=r"(v.z), "=r"(v.w) : "r"(a) : "memory"); return v;
}
__device__ __forceinline__ void mma16816(float (&c)[4], uint32_t a0, uint32_t a1, uint32_t a2, uint32_t a3, uint32_t b0, uint32_t b1) {
    asm volatile("mma.sync.aligned.m16n8k16.row.col.f32.bf16.bf16.f32 {%0,%1,%2,%3}, {%4,%5,%6,%7}, {%8,%9}, {%0,%1,%2,%3};"
        : "+f"(c[0]), "+f"(c[1]), "+f"(c[2]), "+f"(c[3]) : "r"(a0), "r"(a1), "r"(a2), "r"(a3), "r"(b0), "r"(b1));
}
__device__ __forceinline__ void pack_acc(uint32_t (&h)[20], const float (&d)[40]) {
#pragma unroll
    for (int i = 0; i < 20; ++i) h[i] = pack_bf16(d[2 * i], d[2 * i + 1]);
}
__device__ __forceinline__ void store_tile(const uint32_t (&h)[20], uint32_t tile, int mt, int w4, int lane) {
    const int r = lane & 7;
    const uint32_t base = tile + mt * KB + (((lane >> 4) * 8 + r) * 128) + (((2 * w4 + ((lane >> 3) & 1)) ^ r) << 4);
#pragma unroll
    for (int i = 0; i < 5; ++i) stsm4t(base + i * 2048, h[4 * i], h[4 * i + 1], h[4 * i + 2], h[4 * i + 3]);
}
__device__ __forceinline__ void fma8(float (&a)[8], float w, const uint4& v) {
    a[0] = fmaf(w, blo(v.x), a[0]); a[1] = fmaf(w, bhi(v.x), a[1]);
    a[2] = fmaf(w, blo(v.y), a[2]); a[3] = fmaf(w, bhi(v.y), a[3]);
    a[4] = fmaf(w, blo(v.z), a[4]); a[5] = fmaf(w, bhi(v.z), a[5]);
    a[6] = fmaf(w, blo(v.w), a[6]); a[7] = fmaf(w, bhi(v.w), a[7]);
}
__device__ __forceinline__ float dot8(const float (&q)[8], const uint4& v) {
    float s = q[0] * blo(v.x);
    s = fmaf(q[1], bhi(v.x), s); s = fmaf(q[2], blo(v.y), s); s = fmaf(q[3], bhi(v.y), s);
    s = fmaf(q[4], blo(v.z), s); s = fmaf(q[5], bhi(v.z), s); s = fmaf(q[6], blo(v.w), s); s = fmaf(q[7], bhi(v.w), s);
    return s;
}
__device__ __forceinline__ uint4 pack8(const float (&a)[8], float s) {
    return make_uint4(pack_bf16(a[0] * s, a[1] * s), pack_bf16(a[2] * s, a[3] * s), pack_bf16(a[4] * s, a[5] * s), pack_bf16(a[6] * s, a[7] * s));
}
__device__ __forceinline__ uint32_t tile_chunk(uint32_t tile, int r, int c) {
    return tile + (c >> 3) * KB + r * 128 + (((c & 7) ^ (r & 7)) << 4);
}
__device__ __forceinline__ uint32_t wsum4(const uint32_t (&a)[4], uint32_t r0, uint32_t r1, uint32_t r2, uint32_t r3) {
    uint32_t z;
    asm("{\n.reg .b32 t;\nmul.rn.bf16x2 t, %1, %5;\nfma.rn.bf16x2 t, %2, %6, t;\nfma.rn.bf16x2 t, %3, %7, t;\nfma.rn.bf16x2 %0, %4, %8, t;\n}"
        : "=r"(z) : "r"(a[0]), "r"(a[1]), "r"(a[2]), "r"(a[3]), "r"(r0), "r"(r1), "r"(r2), "r"(r3));
    return z;
}
__device__ __forceinline__ void softmax4(const float (&s)[4], const float (&u)[4], int lane, uint32_t (&a)[4]) {
    const bool b = lane & 4, c = lane & 8;
    const float k0 = (b ? u[1] : s[0]) + __shfl_xor_sync(0xffffffffu, b ? s[1] : u[0], 4);
    const float k1 = (b ? u[3] : s[2]) + __shfl_xor_sync(0xffffffffu, b ? s[3] : u[2], 4);
    const float e = (c ? k1 : k0) + __shfl_xor_sync(0xffffffffu, c ? k0 : k1, 9);
    float pe;
    asm("ex2.approx.ftz.f32 %0, %1;" : "=f"(pe) : "f"(e * (0.0625f * 1.4426950408889634f)));
    const int l0 = (lane >> 4) * 18;
    const float p0 = __shfl_sync(0xffffffffu, pe, l0), p1 = __shfl_sync(0xffffffffu, pe, l0 + 9);
    const float p2 = __shfl_sync(0xffffffffu, pe, l0 + 4), p3 = __shfl_sync(0xffffffffu, pe, l0 + 13);
    float inv;
    asm("rcp.approx.ftz.f32 %0, %1;" : "=f"(inv) : "f"(((p0 + p1) + (p2 + p3)) + 1e-9f));
    a[0] = pack_bf16(p0 * inv, p0 * inv); a[1] = pack_bf16(p1 * inv, p1 * inv);
    a[2] = pack_bf16(p2 * inv, p2 * inv); a[3] = pack_bf16(p3 * inv, p3 * inv);
}
__device__ __forceinline__ void attention_chunks(const uint4 (&r)[4][2], uint32_t tile, int node, int lane) {
    const uint32_t qa = tile_chunk(tile, node + (lane >> 4), lane & 15);
    const uint4 q0 = lds128(qa), q1 = lds128(qa + 2 * KB);
    float s[4] = {0.f, 0.f, 0.f, 0.f}, u[4] = {0.f, 0.f, 0.f, 0.f};
    mma16816(s, r[0][0].x, r[1][0].x, r[0][0].y, r[1][0].y, q0.x, q0.y); mma16816(u, r[2][0].x, r[3][0].x, r[2][0].y, r[3][0].y, q0.x, q0.y);
    mma16816(s, r[0][0].z, r[1][0].z, r[0][0].w, r[1][0].w, q0.z, q0.w); mma16816(u, r[2][0].z, r[3][0].z, r[2][0].w, r[3][0].w, q0.z, q0.w);
    mma16816(s, r[0][1].x, r[1][1].x, r[0][1].y, r[1][1].y, q1.x, q1.y); mma16816(u, r[2][1].x, r[3][1].x, r[2][1].y, r[3][1].y, q1.x, q1.y);
    mma16816(s, r[0][1].z, r[1][1].z, r[0][1].w, r[1][1].w, q1.z, q1.w); mma16816(u, r[2][1].z, r[3][1].z, r[2][1].w, r[3][1].w, q1.z, q1.w);
    uint32_t a[4];
    softmax4(s, u, lane, a);
#pragma unroll
    for (int h = 0; h < 2; ++h)
        sts128(qa + h * 2 * KB, make_uint4(wsum4(a, r[0][h].x, r[1][h].x, r[2][h].x, r[3][h].x), wsum4(a, r[0][h].y, r[1][h].y, r[2][h].y, r[3][h].y),
                                           wsum4(a, r[0][h].z, r[1][h].z, r[2][h].z, r[3][h].z), wsum4(a, r[0][h].w, r[1][h].w, r[2][h].w, r[3][h].w)));
}
__device__ __forceinline__ void attention_frags(const uint4 (&r)[2][4], uint32_t tile, int node, int lane) {
    const int nd = node + ((lane >> 2) & 1);
    const uint32_t qa = tile + (lane >> 4) * KB + nd * 128 + (((lane ^ (lane >> 1 & 4) ^ nd) & 7) << 4);
    const uint4 q0 = ldsm4(qa), q1 = ldsm4(qa + 2 * KB);
    float s[4] = {0.f, 0.f, 0.f, 0.f}, u[4] = {0.f, 0.f, 0.f, 0.f};
    mma16816(s, r[0][0].x, r[0][0].y, r[0][0].z, r[0][0].w, q0.x, q0.y); mma16816(u, r[1][0].x, r[1][0].y, r[1][0].z, r[1][0].w, q0.x, q0.y);
    mma16816(s, r[0][1].x, r[0][1].y, r[0][1].z, r[0][1].w, q0.z, q0.w); mma16816(u, r[1][1].x, r[1][1].y, r[1][1].z, r[1][1].w, q0.z, q0.w);
    mma16816(s, r[0][2].x, r[0][2].y, r[0][2].z, r[0][2].w, q1.x, q1.y); mma16816(u, r[1][2].x, r[1][2].y, r[1][2].z, r[1][2].w, q1.x, q1.y);
    mma16816(s, r[0][3].x, r[0][3].y, r[0][3].z, r[0][3].w, q1.z, q1.w); mma16816(u, r[1][3].x, r[1][3].y, r[1][3].z, r[1][3].w, q1.z, q1.w);
    uint32_t a[4];
    softmax4(s, u, lane, a);
#pragma unroll
    for (int h = 0; h < 2; ++h)
        stsm4(qa + h * 2 * KB, wsum4(a, r[0][2 * h].x, r[0][2 * h].y, r[1][2 * h].x, r[1][2 * h].y), wsum4(a, r[0][2 * h].z, r[0][2 * h].w, r[1][2 * h].z, r[1][2 * h].w),
              wsum4(a, r[0][2 * h + 1].x, r[0][2 * h + 1].y, r[1][2 * h + 1].x, r[1][2 * h + 1].y), wsum4(a, r[0][2 * h + 1].z, r[0][2 * h + 1].w, r[1][2 * h + 1].z, r[1][2 * h + 1].w));
}
__device__ __noinline__ void attention_generic(const Params& p, uint32_t tile, int nl, int node, int lane) {
    const uint32_t qa = tile_chunk(tile, nl, lane);
    const uint4 qv = lds128(qa);
    const float q[8] = {blo(qv.x), bhi(qv.x), blo(qv.y), bhi(qv.y), blo(qv.z), bhi(qv.z), blo(qv.w), bhi(qv.w)};
    float z[8] = {0.f, 0.f, 0.f, 0.f, 0.f, 0.f, 0.f, 0.f};
    float den = 0.f;
#pragma unroll 1
    for (int e = 0; e < p.Ee; e += 32) {
        const bool m = (e + lane < p.Ee) && (__ldg(p.edst + e + lane) == node);
        const int sv = m ? __ldg(p.esrc + e + lane) : 0;
        uint32_t bal = __ballot_sync(0xffffffffu, m);
        while (bal) {
            const int l = __ffs(bal) - 1; bal &= bal - 1;
            const uint4 v = ldg_in(row_ptr(p.x + lane * 16, __shfl_sync(0xffffffffu, sv, l)));
            float c = dot8(q, v);
#pragma unroll
            for (int o = 16; o; o >>= 1) c += __shfl_xor_sync(0xffffffffu, c, o);
            const float pe = expf(c * 0.0625f);
            den += pe;
            fma8(z, pe, v);
        }
    }
    sts128(qa, pack8(z, 1.f / (den + 1e-9f)));
}
__device__ __noinline__ void local_generic(const Params& p, int node0, int w, int lane) {
    float a0[8], a1[8], a2[8], a3[8];
#pragma unroll
    for (int k = 0; k < 8; ++k) { a0[k] = 0.f; a1[k] = 0.f; a2[k] = 0.f; a3[k] = 0.f; }
#pragma unroll 1
    for (int e = 0; e < p.E; e += 32) {
        const int dl = (e + lane < p.E) ? __ldg(p.dst + e + lane) - node0 - w : -1;
        const int k = dl == 0 ? 0 : dl == AW ? 1 : dl == 2 * AW ? 2 : (dl == 3 * AW && w + 3 * AW < NPC) ? 3 : -1;
        const int sv = k >= 0 ? __ldg(p.src + e + lane) : 0;
        uint32_t bal = __ballot_sync(0xffffffffu, k >= 0);
        while (bal) {
            const int l = __ffs(bal) - 1; bal &= bal - 1;
            const int s = __shfl_sync(0xffffffffu, sv, l), kk = __shfl_sync(0xffffffffu, k, l);
            const uint4 v = ldg_sc(p.H + lane * N + s);
            if (kk & 2) { if (kk & 1) fma8(a3, 1.f, v); else fma8(a2, 1.f, v); }
            else        { if (kk & 1) fma8(a1, 1.f, v); else fma8(a0, 1.f, v); }
        }
    }
    const int n = node0 + w;
    red_row(p.out + n * 32 + lane, pack8(a0, __bfloat162float(p.dis[n])));
    red_row(p.out + (n + AW) * 32 + lane, pack8(a1, __bfloat162float(p.dis[n + AW])));
    red_row(p.out + (n + 2 * AW) * 32 + lane, pack8(a2, __bfloat162float(p.dis[n + 2 * AW])));
    if (w + 3 * AW < NPC) red_row(p.out + (n + 3 * AW) * 32 + lane, pack8(a3, __bfloat162float(p.dis[n + 3 * AW])));
}
__device__ __forceinline__ uint32_t hadd2(uint32_t a, uint32_t b) { uint32_t d; asm("add.rn.bf16x2 %0, %1, %2;" : "=r"(d) : "r"(a), "r"(b)); return d; }
__device__ __forceinline__ float plo(uint32_t v) { uint32_t d; asm("prmt.b32 %0, %1, 0, 0x1044;" : "=r"(d) : "r"(v)); return __uint_as_float(d); }
template <int HI, int NR>
__device__ __forceinline__ uint32_t agg_sum(uint32_t w, uint32_t base) {
    uint32_t a, r0, r1, r2, r3;
    if (HI) asm("dp2a.hi.u32.u32 %0, %1, %2, %3;" : "=r"(a) : "r"(w), "r"(0x10000010u), "r"(base));
    else    asm("dp2a.lo.u32.u32 %0, %1, %2, %3;" : "=r"(a) : "r"(w), "r"(0x10000010u), "r"(base));
    if (NR == 2) {
        asm volatile("ldmatrix.sync.aligned.m8n8.x2.shared.b16 {%0,%1}, [%2];" : "=r"(r0), "=r"(r1) : "r"(a));
        return hadd2(r0, r1);
    }
    asm volatile("ldmatrix.sync.aligned.m8n8.x4.shared.b16 {%0,%1,%2,%3}, [%4];" : "=r"(r0), "=r"(r1), "=r"(r2), "=r"(r3) : "r"(a));
    return hadd2(hadd2(r0, r1), hadd2(r2, r3));
}
struct Unit { uint4 a, b; };
__device__ __forceinline__ uint32_t unit_stale(const Unit& x, uint32_t lt) {
    if (CHK1) return ((x.a.x ^ lt) | (x.b.x ^ lt)) & 0xc000u;
    const uint32_t o = x.a.x | x.a.y | x.a.z | x.a.w | x.b.x | x.b.y | x.b.z | x.b.w, a = x.a.x & x.a.y & x.a.z & x.a.w & x.b.x & x.b.y & x.b.z & x.b.w;
    return ((o ^ lt) | (a ^ lt)) & 0xc000u;
}
__device__ __forceinline__ uint32_t agg_tail(float lo, float hi, uint32_t s, const uint4& w, uint32_t base, uint32_t b5, uint32_t b6) {
    if (b5 > 0xffffu) {
        s = hadd2(s, agg_sum<1, 4>(w.z, base));
        if (b6) {
            const uint32_t u = b6 > 0xffffu ? agg_sum<0, 4>(w.w, base) : agg_sum<0, 2>(w.w, base);
            lo += plo(u); hi += bhi(u);
        }
    } else if (b5) s = hadd2(s, agg_sum<1, 2>(w.z, base));
    const float f = bhi(w.w);
    return pack_bf16((lo + plo(s)) * f, (hi + bhi(s)) * f);
}
__device__ __forceinline__ void agg_unit(const Unit& x, uint32_t base, uint32_t stg, uint32_t lt) {
    const uint32_t s0 = hadd2(agg_sum<0, 4>(x.a.x, base), agg_sum<1, 4>(x.a.x, base)), u0 = hadd2(agg_sum<0, 4>(x.b.x, base), agg_sum<1, 4>(x.b.x, base));
    const uint32_t s1 = hadd2(agg_sum<0, 4>(x.a.y, base), agg_sum<1, 4>(x.a.y, base)), u1 = hadd2(agg_sum<0, 4>(x.b.y, base), agg_sum<1, 4>(x.b.y, base));
    const uint32_t s2 = agg_sum<0, 4>(x.a.z, base), u2 = agg_sum<0, 4>(x.b.z, base);
    const uint32_t a5 = __ballot_sync(0xffffffffu, x.a.z > (lt | 0xffffu)), a6 = __ballot_sync(0xffffffffu, x.a.w & 0x3fffu);
    const uint32_t b5 = __ballot_sync(0xffffffffu, x.b.z > (lt | 0xffffu)), b6 = __ballot_sync(0xffffffffu, x.b.w & 0x3fffu);
    const uint32_t oa = agg_tail(plo(s0) + plo(s1), bhi(s0) + bhi(s1), s2, x.a, base, a5, a6);
    const uint32_t ob = agg_tail(plo(u0) + plo(u1), bhi(u0) + bhi(u1), u2, x.b, base, b5, b6);
    asm volatile("stmatrix.sync.aligned.m8n8.x2.shared.b16 [%0], {%1,%2};" :: "r"(stg), "r"(oa), "r"(ob) : "memory");
}

__global__ void __launch_bounds__(NTHR, 1)
fused_kernel(const __grid_constant__ Params p,
             const __grid_constant__ CUtensorMap tmX, const __grid_constant__ CUtensorMap tmWl,
             const __grid_constant__ CUtensorMap tmM, const __grid_constant__ CUtensorMap tmWv,
             const __grid_constant__ CUtensorMap tmR, const __grid_constant__ CUtensorMap tmO,
             const __grid_constant__ CUtensorMap tmG, const __grid_constant__ CUtensorMap tmQ,
             const __grid_constant__ CUtensorMap tmK, const __grid_constant__ CUtensorMap tmV3)
{
    extern __shared__ __align__(1024) unsigned char smem[];
    const uint32_t sb = s32(smem);
    const int tid = threadIdx.x, lane = tid & 31;
    const int warp = __shfl_sync(0xffffffffu, tid >> 5, 0);
    const int cta = blockIdx.x;
    const int node0 = cta * NPC;
    const bool rowcta = cta < RCTA;
    const int slice = cta >> 2, quarter = cta & 3;
    const int nlast = 12 + (quarter == 3);
    const int i0 = (cta >> 3) * 16, j0 = (cta & 7) * 32;
    const uint32_t bars = sb + SM_MISC;
    const uint32_t sS = sb + SM_S, sT = sb + SM_T;

    const bool stage = rowcta && !p.force_eslow;
    auto slow_cta = [&]() { uint32_t a, b; asm volatile("ld.shared.v2.u32 {%0, %1}, [%2];" : "=r"(a), "=r"(b) : "r"(bars + MI_SLOW) : "memory"); return a || b > OVCAP; };
    auto publish = [&](int set) {
        const uint4 dv = lds128(bars + MI_DIS + set * 16);
        uint4 v = lds128(sb + X_IMG + set * 512 + lane * 16);
        const uint4 z = lds128(sb + X_DEF + set * 64 + (lane & 3) * 16);
        if ((lane & 3) == 3) { v.x = __byte_perm(v.x, v.y, 0x5410); v.y = v.w; }
        v.x = __vmaxu2(v.x, z.x); v.y = __vmaxu2(v.y, z.y); v.z = __vmaxu2(v.z, z.z); v.w = __vmaxu2(v.w, z.w);
        if (slow_cta()) v = make_uint4(0, 0, 0, 0);
        const uint32_t lt = list_tag(lds32(bars + MI_EPOCH));
        v.x |= lt; v.y |= lt; v.z |= lt; v.w |= lt;
        if ((lane & 3) == 3) { const uint32_t sel = lane & 16 ? 0x7632 : 0x5410; v.z = __byte_perm(dv.x, dv.y, sel); v.w = __byte_perm(dv.z, dv.w, sel); }
        uint32_t* ip = (uint32_t*)p.idx + (cta * 10 + set) * 128 + lane;
        st_relaxed(ip, __byte_perm(v.x, v.z, 0x5410));      st_relaxed(ip + 32, __byte_perm(v.x, v.z, 0x7632));
        st_relaxed(ip + 64, __byte_perm(v.y, v.w, 0x5410)); st_relaxed(ip + 96, __byte_perm(v.y, v.w, 0x7632));
    };

    if (warp >= AW) {
        const int pw = warp - AW;
        if (elect()) {
            auto init = [&](int b0, int b1, int c) {
#pragma unroll
                for (int b = b0; b < b1; b += 8) mbar_init(bars + b, c);
            };
            if (pw == 0)      { PROF(0); prefetch_map(&tmQ); prefetch_map(&tmK); prefetch_map(&tmX); prefetch_map(&tmWl); init(B_K, B_A, 1); }
            else if (pw == 1) { init(B_A, B_F, 4); mbar_init(bars + B_S, 6); mbar_init(bars + B_VE, GW); mbar_init(bars + B_Z, AW); }
            else if (pw == 2) { init(B_F, B_GO, GW); init(B_FA, B_S, 8); }
            else              { init(B_GO, B_Z, 1); init(B_RND, B_RND + 96, 12); mbar_init(bars + B_RND + 96, nlast); }
            asm volatile("fence.mbarrier_init.release.cluster;" ::: "memory");
        }
        bar_arrive(4, LT + 128);
        if (pw) bar_sync(0, GT + 128); else bar_arrive(0, GT + 128);
        auto load_units = [&](const CUtensorMap* tm, int kq, int slot) {
            if (elect()) { mbar_expect(bars + B_K + kq * 8, 4 * UNIT); tma3d(sS + slot * UNIT, tm, kq * 64, bars + B_K + kq * 8); }
        };
        const int v0 = pw ? pw - 2 : 2;
        auto tile_rows = [&](uint2 (&e)[6], int c) {
#pragma unroll
            for (int n = 0; n < 6; ++n) {
                const int v = min(v0 + 3 * n, 15);
                asm volatile("ld.shared.v2.u32 {%0, %1}, [%2];" : "=r"(e[n].x), "=r"(e[n].y) : "r"(bars + MI_ES + ((v >> 2) * 16 + c * 4 + (v & 3)) * 8) : "memory");
            }
        };
        auto stage_tiles = [&](const uint2 (&e)[6], int c) {
            mbar_wait(bars + (c ? B_F + 32 + c * 8 : T0BAR), 0);
            if (elect()) {
#pragma unroll
                for (int n = 0; n < 6; ++n) {
                    const int v = v0 + 3 * n;
                    if (n < 5 || v < 16) {
                        const uint32_t dst = sS + (A_TILES >> (8 * c) & 255) * UNIT + v * 2048, bar = bars + B_A + ((v & 12) + c) * 8;
                        mbar_expect(bar, 2048);
                        tma2d(dst, &tmG, 0, e[n].x & 0xffffu, bar);        tma2d(dst + 512, &tmG, 0, e[n].x >> 16, bar);
                        tma2d(dst + 1024, &tmG, 0, e[n].y & 0xffffu, bar); tma2d(dst + 1536, &tmG, 0, e[n].y >> 16, bar);
                    }
                }
            }
            if (pw == 2 && lane == 0) PROF(45 + c);
        };
        if (pw == 0) {
            if (elect()) {
                mbar_expect(bars + B_QK, 3 * UNIT);
                tma3d(sS + A3 * UNIT, &tmQ, i0, bars + B_QK);
                tma3d(sS + (A3 + 1) * UNIT, &tmK, j0, bars + B_QK);
                if (rowcta) {
#pragma unroll
                    for (int kq = 0; kq < 4; ++kq) {
                        mbar_expect(bars + B_K + kq * 8, KB + 4 * UNIT);
                        tma2d(sT + kq * KB, &tmX, kq * 64, node0, bars + B_K + kq * 8);
                        tma3d(sS + (kq == 0 ? A0 : kq == 1 ? A1 : kq == 2 ? A2 : A4) * UNIT, &tmWl, kq * 64, bars + B_K + kq * 8);
                    }
                    PROF(3);
                    prefetch_map(&tmM); prefetch_map(&tmG); prefetch_map(&tmWv); prefetch_map(&tmV3); prefetch_map(&tmR);
                }
            }
        }
        if (pw >= 2 && stage) {
            const uint4 e = ldg_in(p.esrc + (node0 + 32 * (pw - 2) + lane) * 4);
            asm volatile("st.shared.v2.u32 [%0], {%1, %2};" :: "r"(bars + MI_ES + ((pw - 2) * 32 + lane) * 8), "r"(e.x | e.y << 16), "r"(e.z | e.w << 16) : "memory");
        }
        if (pw != 1 && rowcta) {
            bar_sync(5, 96);
            uint2 e[4][6];
#pragma unroll
            for (int c = 0; c < 4 - G3; ++c) tile_rows(e[c], c);
            mbar_wait(bars + B_EPO, 0);
            mbar_wait(bars + B_F, 0);
#pragma unroll 1
            for (int c = 0; c < 4 - G3; ++c) {
                if (pw == 0 && c == 0) {
                    mbar_wait(bars + B_CGO, 0);
                    wait_count(p.sync + SY_M, (lds32(bars + MI_EPOCH) + 1) * NCTA);
                    fence_async_gmem();
                    if (lane == 0) PROF(2);
                    load_units(&tmM, 0, A0);
                    if (lane == 0) PROF(39);
                    mbar_wait(bars + B_F + 8, 0);  load_units(&tmM, 1, A1);
                    mbar_wait(bars + B_F + 16, 0); load_units(&tmM, 2, A2);
                    warp_arrive(bars + B_MI);
                    if (lane == 0) PROF(40);
                }
                if (pw == 0 && c == 1) { mbar_wait(bars + B_F + 32, 0); load_units(&tmM, 3, A0); }
                if (stage) stage_tiles(e[0], c);
#pragma unroll
                for (int n = 0; n < 6; ++n) { e[0][n] = e[1][n]; e[1][n] = e[2][n]; if (!G3) e[2][n] = e[3][n]; }
            }
        }
        if (pw == 0) {
            if (rowcta) {
                if (HRW) mbar_wait(bars + B_HR, 0);
                mbar_wait(bars + B_FA, 0);      fence_async_smem();  load_units(&tmWv, 0, A3);
                mbar_wait(bars + B_FA + 8, 0);  fence_async_smem();  load_units(&tmWv, 1, A1);
                mbar_wait(bars + B_FA + 16, 0); fence_async_smem();  load_units(&tmWv, 2, A2);
                mbar_wait(bars + B_HR, 0);
                mbar_wait(bars + B_XF, 0);      fence_async_smem();
                if (elect()) {
                    mbar_expect(bars + B_K + 24, 4 * UNIT);
#pragma unroll
                    for (int ks = 0; ks < 4; ++ks) tma3d(sS + (A5 + ks) * UNIT, &tmV3, 192 + ks * 16, bars + B_K + 24);
                }
                if (lane == 0) PROF(5);
                const int novf = slow_cta() ? 0 : lds32(bars + MI_NOVF);
                if (novf) { mbar_wait(bars + B_S, 0); mbar_wait(bars + B_RGO, 0); }
#pragma unroll 1
                for (int o = 0; o < novf; ++o) {
                    const uint32_t w = lds32(bars + MI_OVF + o * 4);
                    const int n = node0 + ((w >> 20) & 127u);
                    float a[8] = {0.f, 0.f, 0.f, 0.f, 0.f, 0.f, 0.f, 0.f};
                    fma8(a, 1.f, ldg_sc(p.H + lane * N + (w & 0x3fffu) - 8));
                    red_row(p.out + n * 32 + lane, pack8(a, __bfloat162float(p.dis[n])));
                }
            }
        } else if (pw == 1) {
            if (rowcta && lane < 10) sts128(bars + MI_DIS + lane * 16, ldg_in(p.dis + node0 + lane * 8));
            bar_sync(3, 128 + 32);
            mbar_wait(bars + B_SENT, 0);
            if (elect()) { PROF(38); red_release(p.sync + SY_M); PROF(1); mbar_arrive(bars + B_CGO); }
            if (VPF && lane < 8) asm volatile("prefetch.global.L2 [%0];" :: "l"(p.wv + (cta * 8 + lane) * 128));
            mbar_wait(bars + B_EPO, 0);
            if (rowcta) {
                mbar_wait(bars + B_HS, 0);
                mbar_wait(bars + B_LF, 0);
                fence_async_smem();
                mbar_wait(bars + B_MI, 0);
                if (HGATE >= 0) mbar_wait(bars + B_K + HGATE * 8, 1);
                uint32_t tn = clk();
#pragma unroll 1
                for (int s = 0; s < 32; s += 2) {
                    wait_clk(tn); tn += HPER;
                    if (elect()) {
                        bulk_store(p.H + s * N + node0, sS + A4 * UNIT + s * 1280, 1280);
                        bulk_store(p.H + (s + 1) * N + node0, sS + A4 * UNIT + s * 1280 + 1280, 1280);
                    }
                }
#pragma unroll 1
                for (int z = cta; z < ER * AW * 16; z += RCTA) {
                    wait_clk(tn); tn += HPER;
                    if (elect()) bulk_store(p.out + ((z & 3) * (UPQ * 16) + (z >> 2) * 4) * 32, sb + X_ZERO, 2048);
                }
                if (elect()) {
                    bulk_commit();
                    asm volatile("cp.async.bulk.wait_group 0;" ::: "memory");
                    PROF(43);
                    fence_async_gmem();
                    red_release(p.sync + SY_H);
                    mbar_arrive(bars + B_HR);
                    PROF(31);
                }
            }
            wait_count(p.sync + SY_H, (lds32(bars + MI_EPOCH) + 1) * RCTA);
            fence_async_gmem();
            if (lane == 0) PROF(6);
            const char* hs = (const char*)(p.H + slice * N) - 128;
            auto chunk = [&](int bar, int lo, int hi) {
                if (rowcta && bar) mbar_wait(bars + bar, 0);
                if (bar >= B_FA) fence_async_smem();
                if (lo == 128) { if (lane < 8) sts128(sS + lane * 16, make_uint4(0, 0, 0, 0)); __syncwarp(); }
                if (elect()) { mbar_expect(bars + B_S, hi - lo); bulk_load(sS + lo, hs + lo, hi - lo, bars + B_S); }
            };
            chunk(0, A4 * UNIT, A5 * UNIT);
            chunk(B_FA + 24, 128, 4 * UNIT);
            chunk(B_F + 64, A3 * UNIT, (A3 + 4) * UNIT);
            chunk(B_F + 72, A1 * UNIT, (A1 + 4) * UNIT);
            chunk(B_F + 80, A2 * UNIT, (A2 + 4) * UNIT);
            chunk(B_F + 88, A5 * UNIT, SLICE_END);
            if (lane == 0) PROF(7);
        } else {
            mbar_wait(bars + B_EPO, 0);
            const uint32_t epoch1 = lds32(bars + MI_EPOCH) + 1;
            if (pw == 2) {
                if (rowcta) {
                    uint32_t early = 0;
#pragma unroll
                    for (int r = 0; r < 5; ++r) { const int u = cta * 5 + r; early |= (u - min(u / UPQ, 3) * UPQ < ER * AW) << r; }
                    auto put_r = [&](bool add) {
#pragma unroll 1
                        for (int r = 0; r < 5; ++r) {
                            const int u = cta * 5 + r;
                            if ((early >> r & 1) == add) {
                                if (elect()) {
#pragma unroll
                                    for (int kb = 0; kb < 4; ++kb) {
                                        if (add) tma2d_add(&tmR, sT + kb * KB + r * 2048, kb * 64, u * 16);
                                        else     tma2d_store(&tmR, sT + kb * KB + r * 2048, kb * 64, u * 16);
                                    }
                                }
                                if (RPER && add) wait_clk(clk() + RPER);
                            }
                        }
                        bulk_commit();
                    };
                    mbar_wait(bars + B_R, 0);
                    fence_async_smem();
                    put_r(false);
                    if (elect()) {
                        asm volatile("cp.async.bulk.wait_group 0;" ::: "memory");
                        fence_async_gmem();
                        red_release(p.sync + SY_R);
                        mbar_arrive(bars + B_RGO);
                        PROF(22);
                    }
                    mbar_wait(bars + B_S, 0);
                    put_r(true);
                    bulk_wait_read<0>();
                    if (lane == 0) PROF(41);
                }
                warp_arrive(bars + B_TF);
            } else {
                if (lane == 0) prefetch_map(&tmO);
                mbar_wait(bars + B_XF, 0);
                if (elect()) red_relaxed(p.sync + SY_L);
                wait_count(p.sync + SY_L, epoch1 * NCTA);
                warp_arrive(bars + B_GO);
                if (lane == 0) PROF(42);
                if (cta == 0 && lane < 16) *(volatile uint32_t*)(p.sync + lane * 32) = epoch1;
#pragma unroll 1
                for (int i = 0; i < 13; ++i) {
                    if (i == 2 * ER) {
                        wait_count(p.sync + SY_R, epoch1 * RCTA);
                        fence_async_gmem();
                        if (lane == 0) PROF(23);
                    }
                    mbar_wait(bars + B_RND + i * 8, 0);
                    fence_async_smem();
                    if (elect()) {
                        tma2d_add(&tmO, sb + SM_X + i * 3072, slice * 8, quarter * (UPQ * 16) + i * 192);
                        if (i == 12 && quarter == 3) tma2d_add(&tmO, sb + SM_X + 13 * 3072, slice * 8, 3 * (UPQ * 16) + 13 * 192);
                    }
                    if (lane == 0 && !(i & 1)) PROF(53 + (i >> 1));
                }
                bulk_commit();
                if (lane == 0) PROF(8);
                bulk_wait_read<0>();
                if (lane == 0) PROF(9);
            }
        }
    } else {
        const int g = lane >> 2, t = lane & 3;
        const int wi = warp < GW ? warp + LW : warp - GW;
        Unit x0, x1;
        const uint4* ip;
        auto fetch = [&](Unit& x, int j) { x.a = ld_relaxed4(ip + j * 64); x.b = ld_relaxed4(ip + j * 64 + 32); };
        auto fetch0 = [&]() { int l = lane; asm volatile("" : "+r"(l)); ip = p.idx + quarter * (UPQ * 64) + l; fetch(x0, wi); };
        if (warp < GW) {
            const int wg = warp >> 2, w4 = warp & 3;
            uint32_t h[20];
            if (rowcta) {
#pragma unroll
                for (int j = 0; j < 10; ++j) h[j] = __ldg((const uint32_t*)p.dis + (node0 >> 1) + 4 * j + t);
            }
            bar_sync(0, GT + 128);
            {
                const uint32_t qa = sS + A3 * UNIT + wg * 2048 + (lane & 15) * 128 + (((lane >> 4) ^ (lane & 7)) << 4);
                const uint32_t ka = sS + (A3 + 1) * UNIT + wg * 4096 + (w4 * 8 + (lane & 7)) * 128 + (((lane >> 3) ^ (lane & 7)) << 4);
                mbar_wait(bars + B_QK, 0);
                __syncwarp();
                if (tid == 0) PROF(33);
                const uint4 b0 = ldsm4(ka), b1 = ldsm4(ka ^ 64), a0 = ldsm4(qa), a1 = ldsm4(qa ^ 32), a2 = ldsm4(qa ^ 64), a3 = ldsm4(qa ^ 96);
                float c[4] = {0.f, 0.f, 0.f, 0.f}, e[4] = {0.f, 0.f, 0.f, 0.f};
                mma16816(c, a0.x, a0.y, a0.z, a0.w, b0.x, b0.y); mma16816(e, a1.x, a1.y, a1.z, a1.w, b0.z, b0.w);
                mma16816(c, a2.x, a2.y, a2.z, a2.w, b1.x, b1.y); mma16816(e, a3.x, a3.y, a3.z, a3.w, b1.z, b1.w);
                float* red = (float*)(smem + SM_X);
                *(float2*)(red + (wg * 16 + g) * 32 + (((w4 + g) & 3) * 8) + 2 * t)     = make_float2(c[0] + e[0], c[1] + e[1]);
                *(float2*)(red + (wg * 16 + g + 8) * 32 + (((w4 + g) & 3) * 8) + 2 * t) = make_float2(c[2] + e[2], c[3] + e[3]);
                bar_sync(1, GT);
                if (wg == 0) {
                    const float* rp = red + (tid >> 3) * 32 + (((tid & 7) * 4 + (tid & 24)) & 31);
                    const float4 v0 = *(const float4*)rp, v1 = *(const float4*)(rp + 512), v2 = *(const float4*)(rp + 1024), v3 = *(const float4*)(rp + 1536);
                    p.M[(i0 + (tid >> 3)) * 64 + (j0 >> 2) + (tid & 7)] =
                        make_uint2(pack_bf16((v0.x + v1.x) + (v2.x + v3.x), (v0.y + v1.y) + (v2.y + v3.y)),
                                   pack_bf16((v0.z + v1.z) + (v2.z + v3.z), (v0.w + v1.w) + (v2.w + v3.w)));
                    bar_arrive(3, 128 + 32);
                }
            }
            if (rowcta) {
                float d[40];
                const uint32_t uw = sS + wg * UNIT, fb = bars + B_F;
                fence_async_smem();
                if (GSENT) mbar_wait(bars + B_SENT, 0);
                gemm_quarter<0>(d, uw + A0 * UNIT, sT, bars + B_K, 0);
                if (tid == 0) PROF(10);
                gemm_quarter<1>(d, uw + A1 * UNIT, sT, bars + B_K, 0, fb);
                gemm_quarter<2>(d, uw + A2 * UNIT, sT, bars + B_K, 0, fb + 8);
                gemm_quarter<3>(d, uw + A4 * UNIT, sT, bars + B_K, 0, fb + 16);
                wg_wait<0>(); warp_arrive(fb + 24);
                if (tid == 0) PROF(11);
#pragma unroll
                for (int j = 9; j >= 0; --j) {
                    const float s0 = blo(h[j]), s1 = bhi(h[j]);
                    h[2 * j + 1] = pack_bf16(d[4 * j + 2] * s0, d[4 * j + 3] * s1);
                    h[2 * j]     = pack_bf16(d[4 * j] * s0, d[4 * j + 1] * s1);
                }
                mbar_wait(fb + 24, 0);
                __syncwarp();
                {
                    const uint32_t sa = sS + A4 * UNIT + warp * 2560 + (lane & 8) * 160 + (lane >> 4) * 128 + (lane & 7) * 16;
#pragma unroll
                    for (int i = 0; i < 5; ++i) stsm4t(sa + i * 256, h[4 * i], h[4 * i + 1], h[4 * i + 2], h[4 * i + 3]);
                }
                warp_arrive(bars + B_HS);
                uint4 e3 = make_uint4(0, 0, 0, 0);
                if (G3 && stage) e3 = ldg_in(p.esrc + (node0 + 16 * wg + 12 + w4) * 4);
                gemm_quarter<0>(d, uw + A0 * UNIT, sT, bars + B_K, 1);
                if (tid == 0) PROF(12);
                gemm_quarter<1>(d, uw + A1 * UNIT, sT, bars + B_K, 1, fb + 32);
                gemm_quarter<2>(d, uw + A2 * UNIT, sT, bars + B_K, 1, fb + 40);
                gemm_quarter<3>(d, uw + A0 * UNIT, sT, bars + B_K, 1, fb + 48);
                if (tid == 0) PROF(13);
                wg_wait<0>(); warp_arrive(fb + 56);
                if (tid == 0) PROF(14);
                pack_acc(h, d);
                mbar_wait(fb + 56, 0);
                __syncwarp();
                store_tile(h, sT, wg, w4, lane);
                warp_arrive(bars + B_Q);
                mbar_wait(bars + B_LF, 0);
                const bool fast = !lds32(bars + MI_EBAD);
                auto stage3 = [&]() {
                    if (G3 && stage && elect()) {
                        const uint32_t dst = uw + A0 * UNIT + w4 * 2048, bar = bars + B_A + (4 * wg + 3) * 8;
                        mbar_expect(bar, 2048);
                        tma2d(dst, &tmG, 0, e3.x, bar);        tma2d(dst + 512, &tmG, 0, e3.y, bar);
                        tma2d(dst + 1024, &tmG, 0, e3.z, bar); tma2d(dst + 1536, &tmG, 0, e3.w, bar);
                    }
                };
                const uint32_t rows = uw + (w4 & 1) * 4096 + (lane & 4) * 512 + (lane & 8) * 64 + (((lane ^ (lane >> 2 & 4)) & 7) << 4);
#pragma unroll 1
                for (int c = w4 >> 1; c < 4; c += 2) {
                    const int n = 16 * wg + 4 * c + 2 * (w4 & 1);
                    if (stage) mbar_wait(bars + B_A + (4 * wg + c) * 8, 0);
                    if (tid == 0) PROF(c ? 50 : 15);
                    if (tid == 96) PROF(c == 1 ? 51 : 52);
                    if (fast) {
                        const uint32_t ra = rows + (A_TILES >> (8 * c) & 255) * UNIT;
                        uint4 r[2][4];
#pragma unroll
                        for (int kb = 0; kb < 4; ++kb) { r[0][kb] = ldsm4(ra + kb * 128); r[1][kb] = ldsm4(ra + 1024 + kb * 128); }
                        warp_arrive(bars + B_FA + c * 8);
                        if (c < 2) { stage3(); mbar_wait(bars + B_Q, 0); }
                        __syncwarp();
                        attention_frags(r, sT, n, lane);
                    } else {
                        warp_arrive(bars + B_FA + c * 8);
                        if (c < 2) stage3();
                        mbar_wait(bars + B_Q, 0);
                        attention_generic(p, sT, n, node0 + n, lane); attention_generic(p, sT, n + 1, node0 + n + 1, lane);
                    }
                }
                fence_async_smem();
                warp_arrive(bars + B_Z);
                if (tid == 0) PROF(16);
                mbar_wait(bars + B_Z, 0);
                if (tid == 0) PROF(17);
                gemm_quarter<0>(d, uw + A3 * UNIT, sT, bars + B_K, 0);
                gemm_quarter<1>(d, uw + A1 * UNIT, sT, bars + B_K, 0, fb + 64);
                gemm_quarter<2>(d, uw + A2 * UNIT, sT, bars + B_K, 0, fb + 72);
                const bool early = EFETCH && mbar_test(bars + B_GO, 0);
                if (early) { fetch0(); }
                {
                    mbar_wait(bars + B_K + 24, 0);
                    __syncwarp();
                    const uint32_t a = desc_lo(sS + A5 * UNIT + wg * 2048), b = desc_lo(sT) + ((3 * KB) >> 4);
                    wg_fence();
                    wgmma80<false>(d, a, b);            wg_commit(); wg_wait<1>(); warp_arrive(fb + 80);
                    wgmma80<false>(d, a + 512, b + 2);  wg_commit(); wg_wait<1>(); warp_arrive(fb + 88);
                    wgmma80<false>(d, a + 1024, b + 4);
                    wgmma80<false>(d, a + 1536, b + 6); wg_commit();
                }
                wg_wait<0>(); warp_arrive(bars + B_VE);
                if (tid == 0) PROF(18);
                pack_acc(h, d);
                mbar_wait(bars + B_VE, 0);
                __syncwarp();
                store_tile(h, sT, wg, w4, lane);
                warp_arrive(bars + B_R);
                if (!early) { mbar_wait(bars + B_GO, 0); fetch0(); }
                if (tid == 0) PROF(19);
            } else {
                mbar_wait(bars + B_GO, 0);
                fetch0();
            }
        } else {
            const int lw = warp - GW, tl = tid - GT;
            const uint32_t epoch = ld_relaxed(p.sync + (cta & 15) * 32);
            uint32_t dd[5], ss[5];
            {
                const int e0 = cta * p.chunk, e1 = min(e0 + p.chunk, p.Efast);
#pragma unroll
                for (int k = 0; k < 5; ++k) { dd[k] = (RCTA + (lane & 1)) * NPC; ss[k] = 0; }
#pragma unroll
                for (int k = 0; k < 2; ++k) {
                    const int e = e0 + 2 * (tl + k * LT);
                    if (e < e1) {
                        const int2 d = __ldg((const int2*)(p.dst + e)), s = __ldg((const int2*)(p.src + e));
                        dd[2 * k] = d.x; dd[2 * k + 1] = d.y; ss[2 * k] = s.x; ss[2 * k + 1] = s.y;
                    }
                }
                const int e = e0 + 4 * LT + tl;
                if (e < e1) { dd[4] = __ldg(p.dst + e); ss[4] = __ldg(p.src + e); }
            }
            int4 ed = make_int4(0, 0, 0, 0), es = make_int4(0, 0, 0, 0);
            if (stage) {
                if (tl < NPC) ed = __ldg((const int4*)p.edst + node0 + tl);
                es = __ldg((const int4*)p.esrc + node0 + 64 + 2 * lw + (lane >> 4));
            }
            const uint32_t oba = sb + X_OUT + (tl ^ ((tl >> 3) & 7)) * 16;
#pragma unroll
            for (int r = 0; r < 4; ++r) { const uint32_t e = (NPC * 8 + (cta & 3) * 8 + (tl & 7)) << 17; sts128(oba + r * LT * 16, make_uint4(e, e, e, e)); }
            if (tl < 32) sts128(bars + MI_PCNT + tl * 16, make_uint4(0, 0, 0, 0));
            if (tl == 32) { sts32(bars + MI_SLOW, p.force_slow); sts32(bars + MI_EBAD, p.force_eslow); sts32(bars + MI_NOVF, 0); sts32(bars + MI_FLAGS, 0); }
            bar_sync(2, LT);
            if (tl == 0) PROF(34);
            const int zero = lds32(bars + MI_PCNT + 127 * 4);
            {
                uint32_t q[5], c[5], qm = 0;
#pragma unroll
                for (int k = 0; k < 5; ++k) {
                    dd[k] += zero;
                    c[k] = dd[k] / NPC;
                    q[k] = atoms_add(bars + MI_PCNT + c[k] * 4, c[k] < RCTA);
                }
                if (tl == 0) PROF(36);
#pragma unroll
                for (int k = 0; k < 5; ++k) {
                    const uint32_t w = (((dd[k] - c[k] * NPC) * 8 + (ss[k] & 7u)) << 17) + ss[k] + (W_VALID + 8);
                    sts32(sb + X_OUT + c[k] * 128 + (((q[k] ^ c[k] ^ ((q[k] >> 4) * 7)) & 7u) << 4) + ((q[k] >> 1) & 12u), w);
                    qm |= q[k];
                }
                const int nz = node0 + tl + zero;
                const bool ebad = stage && tl < NPC && ((ed.x != nz) | (ed.y != nz) | (ed.z != nz) | (ed.w != nz));
                const uint32_t fl = (ebad ? W_EBAD : 0u) | (qm > 31 ? W_OVF : 0u);
                if (fl) asm volatile("red.shared.or.b32 [%0], %1;" :: "r"(bars + MI_FLAGS), "r"(fl) : "memory");
            }
            if (tl == 0) PROF(37);
            bar_sync(4, LT + 128);
            if (tl == 0) PROF(24);
            const uint32_t tag = ((epoch + zero) % 31u + 1u) << 27;
            {
                const uint32_t fl = lds32(bars + MI_FLAGS) | tag;
                uint4* const gp = p.cells + ((tl >> 3) * NCTA + cta) * 8 + (tl & 7);
#pragma unroll
                for (int r = 0; r < 4; ++r) {
                    uint4 w = lds128(oba + r * LT * 16);
                    w.x |= fl; w.y |= tag; w.z |= tag; w.w |= tag;
                    if (r < 3 || tl + r * LT < RCTA * 8) gp[r * (LT / 8) * NCTA * 8] = w;
                }
            }
            warp_arrive(bars + B_SENT);
            if (tl == 0) { sts32(bars + MI_EPOCH, epoch); mbar_arrive(bars + B_EPO); }
            if (tl == 0) PROF(25);
            uint4 r[4][2];
            auto load_rows = [&]() {
                if (stage) {
                    const char* xl = p.x + (lane & 15) * 16;
                    const char* r0 = row_ptr(xl, es.x); const char* r1 = row_ptr(xl, es.y); const char* r2 = row_ptr(xl, es.z); const char* r3 = row_ptr(xl, es.w);
                    r[0][0] = ldg_in(r0); r[0][1] = ldg_in(r0 + 256); r[1][0] = ldg_in(r1); r[1][1] = ldg_in(r1 + 256);
                    r[2][0] = ldg_in(r2); r[2][1] = ldg_in(r2 + 256); r[3][0] = ldg_in(r3); r[3][1] = ldg_in(r3 + 256);
                }
            };
            if (rowcta) {
                bar_sync(2, LT);
                sts128(sb + X_IMG + tl * 16, make_uint4(0, 0, 0, 0));
                if (tl < (X_TAB - X_IMG) / 16 - LT) sts128(sb + X_IMG + (LT + tl) * 16, make_uint4(0, 0, 0, 0));
                if (tl == LT - 1) sts32(sb + X_TAB + NPC * 64, 64);
                if (tl < 128) sts128(sb + X_ZERO + tl * 16, make_uint4(0, 0, 0, 0));
                bar_sync(2, LT);
                uint4 cw[4];
                const uint4* cp = p.cells + cta * (NCTA * 8) + tl;
                mbar_wait(bars + B_CGO, 0);
                if (LROW == 3) load_rows();
                uint32_t pend = 15u;
#pragma unroll 1
                for (int it = 0; it < SPIN_LIMIT && pend; ++it) {
#pragma unroll
                    for (int m = 0; m < 4; ++m) if (pend >> m & 1u) cw[m] = ld_relaxed4(cp + m * LT);
#pragma unroll
                    for (int m = 0; m < 4; ++m)
                        if (__all_sync(0xffffffffu, (((cw[m].x ^ tag) | (cw[m].y ^ tag) | (cw[m].z ^ tag) | (cw[m].w ^ tag)) >> 27) == 0)) pend &= ~(1u << m);
                }
                if (LROW == 2) load_rows();
                const uint32_t st = cw[0].x | cw[1].x | cw[2].x | cw[3].x;
                if (tl == 0 && st != 77) PROF(26);
                if (st & W_OVF)  sts32(bars + MI_SLOW, 1);
                if (st & W_EBAD) sts32(bars + MI_EBAD, 1);
                const uint32_t none = (NPC * 8 + lane) << 17;
                auto lose = [&](const uint32_t (&w)[8]) {
                    if (__any_sync(0xffffffffu, (int)(w[0] | w[1] | w[2] | w[3] | w[4] | w[5] | w[6] | w[7]) < 0)) {
                        uint32_t n = 0;
#pragma unroll
                        for (int m = 0; m < 8; ++m) n += w[m] >> 31;
                        uint32_t o = atoms_add(bars + MI_NOVF, n);
#pragma unroll
                        for (int m = 0; m < 8; ++m) {
                            if ((int)w[m] < 0) sts32(bars + MI_OVF + min(o, (uint32_t)OVCAP - 1) * 4, w[m]);
                            o += w[m] >> 31;
                        }
                    }
                };
                if (__any_sync(0xffffffffu, (cw[0].z | cw[1].z | cw[2].z | cw[3].z) & W_VALID)) {
#pragma unroll
                    for (int x = 1; x < 3; ++x)
#pragma unroll
                        for (int m = 0; m < 4; ++m)
                            if (!(cw[m ^ x].y & W_VALID)) { cw[m ^ x].y = cw[m].z; cw[m].z = none; }
                    if (__any_sync(0xffffffffu, (cw[0].z | cw[1].z | cw[2].z | cw[3].z | cw[0].w | cw[1].w | cw[2].w | cw[3].w) & W_VALID)) {
                        uint32_t z[8] = {cw[0].z, cw[0].w, cw[1].z, cw[1].w, cw[2].z, cw[2].w, cw[3].z, cw[3].w};
#pragma unroll
                        for (int m = 0; m < 8; ++m) z[m] = (z[m] & W_KEEP) | (z[m] & W_VALID) << 15;
                        lose(z);
                    }
                }
                uint32_t w[8] = {cw[0].x, cw[0].y, cw[1].x, cw[1].y, cw[2].x, cw[2].y, cw[3].x, cw[3].y};
                {
                    uint32_t c[8];
#pragma unroll
                    for (int m = 0; m < 8; ++m) {
                        const uint32_t v = (w[m] >> 16) & 1u;
                        w[m] &= W_KEEP;
                        c[m] = atoms_add(sb + X_CNT + (w[m] >> 15), v);
                    }
#pragma unroll
                    for (int m = 0; m < 8; ++m) w[m] += (c[m] > 7 ? 0x20000u : c[m]) << 14;
                }
                bar_sync(2, LT);
                if (tl == 0) { mbar_arrive(bars + B_LF); PROF(27); }
                if (lw < 3) {
                    const int d0 = min(tl, NPC - 8 + (tl & 7));
                    const int dl = d0 ^ ((d0 >> 3) & 1);
                    const uint4 n0 = lds128(sb + X_CNT + dl * 32), n1 = lds128(sb + X_CNT + dl * 32 + 16);
                    uint32_t pk = min(n0.x, 8u) + (min(n0.y, 8u) << 4) + (min(n0.z, 8u) << 8) + (min(n0.w, 8u) << 12) +
                                  (min(n1.x, 8u) << 16) + (min(n1.y, 8u) << 20) + (min(n1.z, 8u) << 24) + (min(n1.w, 8u) << 28);
                    pk = __funnelshift_r(pk, pk, 4 * lane);
                    uint32_t du = 0xf0000000u, ru = 0, b[8] = {0, 0, 0, 0, 0, 0, 0, 0};
                    auto code2 = [&](uint32_t b0, uint32_t b1) {
                        return __byte_perm(__float_as_uint(__uint_as_float(b0) * 8388608.f), __float_as_uint(__uint_as_float(b1) * 8388608.f), 0x7632);
                    };
                    uint32_t ta = (lane + 7) * 8;
                    auto pass_on = [&]() {
                        ru = __shfl_sync(0xffffffffu, ru, lane + 1, 8);
                        const uint32_t t0 = (code2(b[0], b[2]) >> 7) + code2(b[1], b[3]) * 2, t1 = (code2(b[4], b[6]) >> 7) + code2(b[5], b[7]) * 2;
                        asm volatile("st.shared.v2.u32 [%0], {%1, %2};" :: "r"(sb + X_TAB + ((dl * 64) | (ta & 56))), "r"(t0), "r"(t1) : "memory");
                        ta += 8;
                    };
                    auto take = [&](uint32_t& m, uint32_t& bit, uint32_t n, int c) {
                        asm("{\n.reg .pred p;\n.reg .b32 u;\nsetp.gt.u32 p, %2, %3;\nadd.u32 u, %0, -1;\nlop3.b32 %1, %0, u, 0, 0x30;\n@p and.b32 %0, %0, u;\n}"
                            : "+r"(m), "=r"(bit) : "r"(n), "r"(c));
                    };
#pragma unroll 1
                    for (int k = 0; k < 8; ++k) {
                        const uint32_t n = pk & 15u;
                        const bool big = __any_sync(0xffffffffu, n > 6);
                        pk >>= 4;
                        pass_on();
                        const uint32_t fr = ~(du | ru);
                        uint32_t m = fr;
#pragma unroll
                        for (int c = 0; c < 6; ++c) take(m, b[c], n, c);
                        if (big) { take(m, b[6], n, 6); take(m, b[7], n, 7); }
                        du |= m ^ fr;
                        ru |= m ^ fr;
                    }
                    pass_on();
                    sts32(sb + X_RU + d0 * 4, ru);
                }
                if (tl == 0) PROF(49);
                if (LROW == 0) load_rows();
                bar_sync(2, LT);
                if (tl == 0) PROF(28);
                const int v = LT - 1 - tl;
                if (lw >= 6 && v < 40) {
                    const uint4 b = lds128(sb + X_RU + (v >> 2) * 32), e = lds128(sb + X_RU + (v >> 2) * 32 + 16);
                    const uint32_t f2 = b.x & b.y & b.z & b.w;
                    const uint32_t s0 = (f2 & e.x) | (~f2 & b.x), s1 = (f2 & e.y) | (~f2 & b.y), s2 = (f2 & e.z) | (~f2 & b.z);
                    const uint32_t f1 = s0 & s1, f0 = (f1 & s2) | (~f1 & s0);
                    uint32_t u[4];
#pragma unroll
                    for (int k = 0; k < 4; ++k) {
                        const int sh = (v & 3) * 8 + 2 * k;
                        u[k] = ((((f0 >> sh) & 3u) * 0x8001u) & 0x10001u) + ((((f1 >> sh) & 3u) * 0x10002u) & 0x20002u) + ((((f2 >> sh) & 3u) * 0x20004u) & 0x40004u);
                    }
                    sts128(sb + X_DEF + v * 16, make_uint4(u[0], u[1], u[2], u[3]));
                }
                {
                    uint32_t rd[8];
#pragma unroll
                    for (int m = 0; m < 8; ++m) asm volatile("ld.shared.u8 %0, [%1];" : "=r"(rd[m]) : "r"(sb + X_TAB + min(w[m] >> 14, NPC * 64u)) : "memory");
#pragma unroll
                    for (int m = 0; m < 8; ++m) {
                        rd[m] -= 1;
                        if (rd[m] < 48) sts16(sb + X_IMG + ((w[m] >> 14) & ~63u) + min(rd[m], 31u) * 2, w[m] & 0x3fffu);
                        w[m] |= rd[m] & 0x80000000u;
                    }
                    lose(w);
                }
                if (LROW == 1) load_rows();
                bar_sync(2, LT);
                if (tl == 0) PROF(29);
#pragma unroll 1
                for (int set = lw; set < 10; set += lw >= 3 && lw < 5 ? 5 : 10) publish(set);
            }
            warp_arrive(bars + B_XF);
            if (tl == 0) PROF(30);
            if (rowcta) {
                mbar_wait(bars + B_Q, 0);
                __syncwarp();
                if (!lds32(bars + MI_EBAD)) attention_chunks(r, sT, 64 + 2 * lw, lane);
                else { attention_generic(p, sT, 64 + 2 * lw, node0 + 64 + 2 * lw, lane); attention_generic(p, sT, 65 + 2 * lw, node0 + 65 + 2 * lw, lane); }
                fence_async_smem();
                warp_arrive(bars + B_Z);
                if (tl == 0) PROF(32);
            }
            mbar_wait(bars + B_GO, 0);
            fetch0();
        }
        const uint32_t stg = sb + SM_X + (lane & 15) * 16;
        const uint32_t lt = list_tag(lds32(bars + MI_EPOCH)), base = sS - (lt & 0xffffu) * 16;
        const int nu = UPQ + (quarter == 3);
        int u = wi;
        auto unit = [&](Unit& c, Unit& n) {
#pragma unroll 1
            for (int it = 0;; ++it) {
                if (!__any_sync(0xffffffffu, unit_stale(c, lt) > (it < SPIN_LIMIT ? 0u : 0xffffu))) break;
                fetch(c, u);
            }
            if (u >= 4 * AW) { mbar_wait(bars + B_TF, 0); __syncwarp(); }
            if (u + AW < nu) fetch(n, u + AW);
            agg_unit(c, base, stg + u * 256, lt);
            warp_arrive(bars + B_RND + min((u * 171) >> 11, 12) * 8);
            u += AW;
        };
        mbar_wait(bars + B_S, 0);
        if (rowcta) mbar_wait(bars + B_VE, 0);
        __syncwarp();
        if (tid == 0) PROF(20);
        if (tid == GT) PROF(4);
#pragma unroll 1
        for (;;) {
            unit(x0, x1);
            if (u >= nu) break;
            unit(x1, x0);
            if (u >= nu) break;
        }
        if (tid == 0) PROF(21);
        if (rowcta && slow_cta()) { mbar_wait(bars + B_RGO, 0); local_generic(p, node0, wi, lane); }
    }
    PROF_FLUSH();
}

typedef CUresult (*EncodeFn)(CUtensorMap*, CUtensorMapDataType, cuuint32_t, void*, const cuuint64_t*, const cuuint64_t*,
                             const cuuint32_t*, const cuuint32_t*, CUtensorMapInterleave, CUtensorMapSwizzle,
                             CUtensorMapL2promotion, CUtensorMapFloatOOBfill);

static void make_map(EncodeFn enc, CUtensorMap* m, const void* ptr, int rows, int box_cols, int box_rows) {
    cuuint64_t dims[2] = {(cuuint64_t)D, (cuuint64_t)rows};
    cuuint64_t strides[1] = {(cuuint64_t)D * 2};
    cuuint32_t box[2] = {(cuuint32_t)box_cols, (cuuint32_t)box_rows};
    cuuint32_t es[2] = {1u, 1u};
    enc(m, CU_TENSOR_MAP_DATA_TYPE_BFLOAT16, 2, const_cast<void*>(ptr), dims, strides, box, es, CU_TENSOR_MAP_INTERLEAVE_NONE,
        box_cols == 64 ? CU_TENSOR_MAP_SWIZZLE_128B : CU_TENSOR_MAP_SWIZZLE_NONE,
        box_cols == 64 ? PROMO : CU_TENSOR_MAP_L2_PROMOTION_NONE, CU_TENSOR_MAP_FLOAT_OOB_FILL_NONE);
}
static void make_map3(EncodeFn enc, CUtensorMap* m, const void* ptr, int rows, int box_rows) {
    cuuint64_t dims[3] = {64, (cuuint64_t)rows, 4};
    cuuint64_t strides[2] = {(cuuint64_t)D * 2, 128};
    cuuint32_t box[3] = {64u, (cuuint32_t)box_rows, 4u};
    cuuint32_t es[3] = {1u, 1u, 1u};
    enc(m, CU_TENSOR_MAP_DATA_TYPE_BFLOAT16, 3, const_cast<void*>(ptr), dims, strides, box, es, CU_TENSOR_MAP_INTERLEAVE_NONE,
        CU_TENSOR_MAP_SWIZZLE_128B, CU_TENSOR_MAP_L2_PROMOTION_L2_256B, CU_TENSOR_MAP_FLOAT_OOB_FILL_NONE);
}

}

extern "C" void kernel_launch(void* const* d_in, const int* in_sizes, int n_in, void* d_out, int out_size) {
    using namespace gk;
    (void)n_in; (void)out_size;
    static EncodeFn enc = nullptr;
    static void *m_ptr, *cells_ptr, *sync_ptr, *h_ptr, *idx_ptr;
    if (!enc) {
        void* fn = nullptr;
        cudaDriverEntryPointQueryResult qr;
        cudaGetDriverEntryPoint("cuTensorMapEncodeTiled", &fn, cudaEnableDefault, &qr);
        enc = (EncodeFn)fn;
        cudaGetSymbolAddress(&m_ptr, g_M);
        cudaGetSymbolAddress(&cells_ptr, g_cells);
        cudaGetSymbolAddress(&sync_ptr, g_sync);
        cudaGetSymbolAddress(&h_ptr, g_H);
        cudaGetSymbolAddress(&idx_ptr, g_idx);
        cudaFuncSetAttribute(fused_kernel, cudaFuncAttributeMaxDynamicSharedMemorySize, SM_ALLOC);
    }
    if (in_sizes[5] != N || in_sizes[0] != N * D) return;
    Params p;
    p.src  = (const int*)d_in[1];
    p.dst  = (const int*)d_in[2];
    p.esrc = (const int*)d_in[3];
    p.edst = (const int*)d_in[4];
    p.sync = (uint32_t*)sync_ptr;
    p.x    = (const char*)d_in[0];
    p.dis  = (const __nv_bfloat16*)d_in[5];
    p.wv   = (const char*)d_in[9];
    p.cells = (uint4*)cells_ptr;
    p.H    = (uint4*)h_ptr;
    p.idx  = (uint4*)idx_ptr;
    p.M    = (uint2*)m_ptr;
    p.out  = (uint4*)d_out;
    p.E  = in_sizes[1];
    p.Ee = in_sizes[3];
    p.chunk = (((p.E + NCTA - 1) / NCTA) + 1) & ~1;
    p.force_slow  = (p.chunk > 5 * LT || (p.E & 1)) ? 1 : 0;
    p.force_eslow = (p.Ee != 4 * N) ? 1 : 0;
    p.Efast = p.force_slow ? 0 : p.E;

    CUtensorMap tmX, tmWl, tmM, tmWv, tmR, tmO, tmG, tmQ, tmK, tmV3;
    make_map(enc, &tmX, d_in[0], N, 64, NPC);
    make_map3(enc, &tmWl, d_in[6], D, 64);
    make_map3(enc, &tmM, m_ptr, D, 64);
    make_map3(enc, &tmWv, d_in[9], D, 64);
    make_map(enc, &tmR, d_out, N, 64, 16);
    make_map(enc, &tmO, d_out, N, 8, 192);
    make_map(enc, &tmG, d_in[0], N, 256, 1);
    make_map3(enc, &tmQ, d_in[7], D, 16);
    make_map3(enc, &tmK, d_in[8], D, 32);
    make_map3(enc, &tmV3, d_in[9], D, 16);
    fused_kernel<<<NCTA, NTHR, SM_ALLOC, cudaStreamPerThread>>>(p, tmX, tmWl, tmM, tmWv, tmR, tmO, tmG, tmQ, tmK, tmV3);
}
```

```cpp
#include <cuda_runtime.h>
#include <cuda_bf16.h>
#include <cuda.h>
#include <stdint.h>

#define PROFILE 0

namespace gk {

constexpr int N      = 10000;
constexpr int D      = 256;
constexpr int NPC    = 80;
constexpr int NCTA   = 128;
constexpr int RCTA   = N / NPC;
constexpr int NSET   = N / 8;
constexpr int GW     = 16;
constexpr int LW     = 8;
constexpr int AW     = GW + LW;
constexpr int GT     = GW * 32, LT = LW * 32;
constexpr int NTHR   = (AW + 4) * 32;
constexpr int UPQ    = 156;
constexpr int OVCAP  = 128;
#define SPINB 18
constexpr int SPIN_LIMIT = 1 << SPINB;

constexpr int KB      = NPC * 128;
constexpr int UNIT    = 8192;
constexpr int SM_S    = 0;
constexpr int SM_X    = 20 * UNIT;
constexpr int SM_T    = 23 * UNIT;
constexpr int SM_MISC = SM_T + 4 * KB;
constexpr int SM_END  = SM_MISC + 2464;
constexpr int SLICE_END = 128 + N * 16;
constexpr int X_OUT  = SM_X + UNIT;
constexpr int X_TAB  = X_OUT;
constexpr int X_RU   = X_TAB + NPC * 64 + 16;
constexpr int X_DEF  = X_RU + NPC * 4;
constexpr int X_ZERO = X_OUT + UNIT - 2048;
constexpr int X_IMG  = X_OUT + UNIT;
constexpr int X_CNT  = X_IMG + NPC * 64;
static_assert(X_DEF + 640 <= X_ZERO && X_CNT + NPC * 32 + 128 <= SM_T, "list scratch");
constexpr int B_K = 0, B_QK = 32, B_EPO = 40,
              B_A = 48,
              B_F = 176, B_HS = 272, B_Q = 280, B_R = 288,
              B_GO = 296, B_LF = 304, B_TF = 312, B_RGO = 320, B_CGO = 328, B_MI = 336, B_HR = 344,
              B_Z = 352,
              B_FA = 360, B_XF = 392, B_SENT = 400, B_S = 408, B_VE = 416,
              B_RND = 424;
constexpr int B_HV = 528, B_RV = 536;
constexpr int MI_EPOCH = 544, MI_EBAD = 548, MI_SLOW = 552, MI_NOVF = 556, MI_FLAGS = 560;
constexpr int MI_OVF  = 1280;
constexpr int MI_ES   = 768;
constexpr int MI_PCNT = 1792;
constexpr int MI_DIS  = 2304;
constexpr int A0 = 0, A1 = 4, A2 = 8, A3 = 12, A4 = 16, A5 = 19;
constexpr uint32_t A_TILES = A3 | A1 << 8 | A2 << 16 | A0 << 24;
#define PROMO CU_TENSOR_MAP_L2_PROMOTION_L2_128B
#define EFETCH 1
#define VPF 1
#define RPER 0
#define ER 2
#define G3 1
#define XORD 0x04156273
#define LGATE 1
#define AUNRV 1
constexpr int AUNR = AUNRV;
#define WPROF 0
#define RGATE 0
#define QLF 0
#define MW 2
#define SROT 1
#define HGATE 0
#define CHK1 0
#define HPER 160
#define HRW 1
#define T0BAR B_CGO

constexpr uint32_t W_OVF = 1u << 24, W_EBAD = 1u << 25;
constexpr int CELLN = 20;

__device__ uint4         g_cells[RCTA * NCTA * 4];
__device__ uint4         g_H[32 * N];
__device__ uint4         g_idx[NSET * 32];
__device__ __nv_bfloat16 g_M[D * D];
__device__ uint32_t      g_sync[24 * 32];
constexpr int SY_M = 16 * 32, SY_H = 17 * 32, SY_L = 18 * 32, SY_R = 19 * 32, SY_SLOW = 20 * 32;
#define PROF(i) do {} while (0)
#define PROF_FLUSH() do {} while (0)
constexpr int SM_ALLOC = SM_END;
static_assert(SM_ALLOC <= 232448, "shared memory");

struct Params {
    const int* src; const int* dst;
    uint32_t* sync;
    const int* esrc; const int* edst;
    int Efast, chunk;
    const __nv_bfloat16* dis;
    const char* x; const char* wv;
    uint4* cells; uint2* M;
    int force_slow, force_eslow;
    uint4* idx; uint4* H; uint4* out;
    int E, Ee;
};

__device__ __forceinline__ uint32_t s32(const void* p) { return (uint32_t)__cvta_generic_to_shared(p); }
__device__ __forceinline__ void mbar_init(uint32_t a, uint32_t cnt) { asm volatile("mbarrier.init.shared.b64 [%0], %1;" :: "r"(a), "r"(cnt) : "memory"); }
__device__ __forceinline__ void mbar_arrive(uint32_t a) { asm volatile("mbarrier.arrive.shared.b64 _, [%0];" :: "r"(a) : "memory"); }
__device__ __forceinline__ void mbar_expect(uint32_t a, uint32_t bytes) { asm volatile("mbarrier.arrive.expect_tx.shared.b64 _, [%0], %1;" :: "r"(a), "r"(bytes) : "memory"); }
__device__ __forceinline__ void mbar_wait(uint32_t a, uint32_t parity) {
    uint32_t ok = 0;
#pragma unroll 1
    for (int it = 0; it < SPIN_LIMIT && !ok; ++it)
        asm volatile("{\n.reg .pred p;\nmbarrier.try_wait.parity.shared.b64 p, [%1], %2;\nselp.u32 %0, 1, 0, p;\n}"
                     : "=r"(ok) : "r"(a), "r"(parity) : "memory");
}
__device__ __forceinline__ bool elect() { uint32_t r; asm volatile("{\n.reg .pred p;\nelect.sync _|p, 0xffffffff;\nselp.u32 %0, 1, 0, p;\n}" : "=r"(r) :: "memory"); return r; }
__device__ __forceinline__ void warp_arrive(uint32_t a) {
    asm volatile("{\n.reg .pred p;\nelect.sync _|p, 0xffffffff;\n@p mbarrier.arrive.shared.b64 _, [%0];\n}" :: "r"(a) : "memory");
}
__device__ __forceinline__ void bar_sync(int id, int n)   { __syncwarp(); asm volatile("bar.sync %0, %1;"   :: "r"(id), "r"(n) : "memory"); }
__device__ __forceinline__ void bar_arrive(int id, int n) { __syncwarp(); asm volatile("bar.arrive %0, %1;" :: "r"(id), "r"(n) : "memory"); }
__device__ __forceinline__ void fence_async_smem() { asm volatile("fence.proxy.async.shared::cta;" ::: "memory"); }
__device__ __forceinline__ void fence_async_gmem() { asm volatile("fence.proxy.async.global;" ::: "memory"); }
__device__ __forceinline__ void tma2d(uint32_t dst, const CUtensorMap* tm, int c0, int c1, uint32_t bar) {
    asm volatile("cp.async.bulk.tensor.2d.shared::cluster.global.mbarrier::complete_tx::bytes [%0], [%1, {%3, %4}], [%2];"
                 :: "r"(dst), "l"(tm), "r"(bar), "r"(c0), "r"(c1) : "memory");
}
__device__ __forceinline__ void tma3d(uint32_t dst, const CUtensorMap* tm, int row, uint32_t bar) {
    asm volatile("cp.async.bulk.tensor.3d.shared::cluster.global.mbarrier::complete_tx::bytes [%0], [%1, {%4, %3, %4}], [%2];"
                 :: "r"(dst), "l"(tm), "r"(bar), "r"(row), "r"(0) : "memory");
}
__device__ __forceinline__ void tma2d_store(const CUtensorMap* tm, uint32_t src, int c0, int c1) {
    asm volatile("cp.async.bulk.tensor.2d.global.shared::cta.bulk_group [%0, {%2, %3}], [%1];"
                 :: "l"(tm), "r"(src), "r"(c0), "r"(c1) : "memory");
}
__device__ __forceinline__ void tma2d_add(const CUtensorMap* tm, uint32_t src, int c0, int c1) {
    asm volatile("cp.reduce.async.bulk.tensor.2d.global.shared::cta.add.bulk_group [%0, {%2, %3}], [%1];"
                 :: "l"(tm), "r"(src), "r"(c0), "r"(c1) : "memory");
}
__device__ __forceinline__ void bulk_load(uint32_t dst, const void* src, uint32_t bytes, uint32_t bar) {
    asm volatile("cp.async.bulk.shared::cluster.global.mbarrier::complete_tx::bytes [%0], [%1], %2, [%3];"
                 :: "r"(dst), "l"(src), "r"(bytes), "r"(bar) : "memory");
}
__device__ __forceinline__ void bulk_store(void* dst, uint32_t src, uint32_t bytes) {
    asm volatile("cp.async.bulk.global.shared::cta.bulk_group [%0], [%1], %2;" :: "l"(dst), "r"(src), "r"(bytes) : "memory");
}
__device__ __forceinline__ uint32_t clk() { uint32_t c; asm volatile("mov.u32 %0, %%clock;" : "=r"(c) :: "memory"); return c; }
__device__ __forceinline__ void wait_clk(uint32_t t) { while ((int)(clk() - t) < 0) {} }
__device__ __forceinline__ void bulk_commit() { asm volatile("cp.async.bulk.commit_group;" ::: "memory"); }
template <int K> __device__ __forceinline__ void bulk_wait_read() { asm volatile("cp.async.bulk.wait_group.read %0;" :: "n"(K) : "memory"); }
__device__ __forceinline__ void prefetch_map(const CUtensorMap* tm) { asm volatile("prefetch.tensormap [%0];" :: "l"(tm) : "memory"); }
__device__ __forceinline__ uint4 lds128(uint32_t a) { uint4 v; asm volatile("ld.shared.v4.u32 {%0,%1,%2,%3}, [%4];" : "=r"(v.x), "=r"(v.y), "=r"(v.z), "=r"(v.w) : "r"(a) : "memory"); return v; }
__device__ __forceinline__ void sts128(uint32_t a, uint4 v) { asm volatile("st.shared.v4.u32 [%0], {%1,%2,%3,%4};" :: "r"(a), "r"(v.x), "r"(v.y), "r"(v.z), "r"(v.w) : "memory"); }
__device__ __forceinline__ uint32_t lds32(uint32_t a) { uint32_t v; asm volatile("ld.shared.u32 %0, [%1];" : "=r"(v) : "r"(a) : "memory"); return v; }
__device__ __forceinline__ void sts32(uint32_t a, uint32_t v) { asm volatile("st.shared.u32 [%0], %1;" :: "r"(a), "r"(v) : "memory"); }
__device__ __forceinline__ void sts16(uint32_t a, uint32_t v) { asm volatile("st.shared.u16 [%0], %1;" :: "r"(a), "h"((unsigned short)v) : "memory"); }
__device__ __forceinline__ uint32_t atoms_add(uint32_t a, uint32_t x) { uint32_t v; asm volatile("atom.shared.add.u32 %0, [%1], %2;" : "=r"(v) : "r"(a), "r"(x) : "memory"); return v; }
__device__ __forceinline__ uint32_t ld_relaxed(const uint32_t* p) { uint32_t v; asm volatile("ld.relaxed.gpu.global.u32 %0, [%1];" : "=r"(v) : "l"(p) : "memory"); return v; }
__device__ __forceinline__ uint4 ld_relaxed4(const uint4* p) { uint4 v; asm volatile("ld.relaxed.gpu.global.L1::no_allocate.v4.u32 {%0,%1,%2,%3}, [%4];" : "=r"(v.x), "=r"(v.y), "=r"(v.z), "=r"(v.w) : "l"(p) : "memory"); return v; }
__device__ __forceinline__ uint32_t ld_acquire(const uint32_t* p) { uint32_t v; asm volatile("ld.acquire.gpu.global.u32 %0, [%1];" : "=r"(v) : "l"(p) : "memory"); return v; }
__device__ __forceinline__ void st_relaxed(uint32_t* p, uint32_t v) { asm volatile("st.relaxed.gpu.global.u32 [%0], %1;" :: "l"(p), "r"(v) : "memory"); }
__device__ __forceinline__ void red_relaxed(uint32_t* p) { asm volatile("red.relaxed.gpu.global.add.u32 [%0], 1;" :: "l"(p) : "memory"); }
__device__ __forceinline__ uint32_t list_tag(uint32_t epoch) { return (epoch % 3u + 1u) * 0x40004000u; }
__device__ __forceinline__ void red_release(uint32_t* p) { asm volatile("red.release.gpu.global.add.u32 [%0], 1;" :: "l"(p) : "memory"); }
__device__ __forceinline__ void wait_count(const uint32_t* p, uint32_t target) {
#pragma unroll 1
    for (int it = 0; it < SPIN_LIMIT; ++it)
        if ((int)(ld_acquire(p) - target) >= 0) break;
}
__device__ __forceinline__ bool mbar_test(uint32_t a, uint32_t parity) {
    uint32_t ok;
    asm volatile("{\n.reg .pred p;\nmbarrier.test_wait.parity.shared.b64 p, [%1], %2;\nselp.u32 %0, 1, 0, p;\n}" : "=r"(ok) : "r"(a), "r"(parity) : "memory");
    return __all_sync(0xffffffffu, ok);
}
__device__ __forceinline__ uint4 ldg_in(const void* p) { uint4 v; asm volatile("ld.global.nc.L1::no_allocate.v4.u32 {%0,%1,%2,%3}, [%4];" : "=r"(v.x), "=r"(v.y), "=r"(v.z), "=r"(v.w) : "l"(p)); return v; }
__device__ __forceinline__ uint4 ldg_sc(const void* p) { uint4 v; asm volatile("ld.global.L1::no_allocate.v4.u32 {%0,%1,%2,%3}, [%4];" : "=r"(v.x), "=r"(v.y), "=r"(v.z), "=r"(v.w) : "l"(p) : "memory"); return v; }
__device__ __forceinline__ void red_row(uint4* p, uint4 v) { asm volatile("red.relaxed.gpu.global.add.noftz.v4.bf16x2 [%0], {%1,%2,%3,%4};" :: "l"(p), "r"(v.x), "r"(v.y), "r"(v.z), "r"(v.w) : "memory"); }
__device__ __forceinline__ uint32_t pack_bf16(float lo, float hi) { uint32_t r; asm("cvt.rn.bf16x2.f32 %0, %1, %2;" : "=r"(r) : "f"(hi), "f"(lo)); return r; }
__device__ __forceinline__ float blo(uint32_t v) { return __uint_as_float(v << 16); }
__device__ __forceinline__ float bhi(uint32_t v) { return __uint_as_float(v & 0xffff0000u); }
__device__ __forceinline__ const char* row_ptr(const char* base, uint32_t row) {
    uint64_t r; asm("mad.wide.u32 %0, %1, 512, %2;" : "=l"(r) : "r"(row), "l"((uint64_t)base)); return (const char*)r;
}

constexpr uint32_t DESC_HI = 64u | (1u << 30);
__device__ __forceinline__ uint32_t desc_lo(uint32_t addr) { return ((addr & 0x3FFFF) >> 4) | (1u << 16); }
__device__ __forceinline__ void wg_fence()  { asm volatile("wgmma.fence.sync.aligned;" ::: "memory"); }
__device__ __forceinline__ void wg_commit() { asm volatile("wgmma.commit_group.sync.aligned;" ::: "memory"); }
template <int K> __device__ __forceinline__ void wg_wait() { asm volatile("wgmma.wait_group.sync.aligned %0;" :: "n"(K) : "memory"); }
#define GK_ACC(c) c(d[0]), c(d[1]), c(d[2]), c(d[3]), c(d[4]), c(d[5]), c(d[6]), c(d[7]), c(d[8]), c(d[9]), \
    c(d[10]), c(d[11]), c(d[12]), c(d[13]), c(d[14]), c(d[15]), c(d[16]), c(d[17]), c(d[18]), c(d[19]), \
    c(d[20]), c(d[21]), c(d[22]), c(d[23]), c(d[24]), c(d[25]), c(d[26]), c(d[27]), c(d[28]), c(d[29]), \
    c(d[30]), c(d[31]), c(d[32]), c(d[33]), c(d[34]), c(d[35]), c(d[36]), c(d[37]), c(d[38]), c(d[39])
#define GK_WGMMA(P) "{\n.reg .pred p;\n.reg .b64 da, db;\nsetp.ne.b32 p, " P ", 0;\nmov.b64 da, {%40, %42};\nmov.b64 db, {%41, %42};\n" \
    "wgmma.mma_async.sync.aligned.m64n80k16.f32.bf16.bf16 " \
    "{%0,%1,%2,%3,%4,%5,%6,%7,%8,%9,%10,%11,%12,%13,%14,%15,%16,%17,%18,%19," \
    "%20,%21,%22,%23,%24,%25,%26,%27,%28,%29,%30,%31,%32,%33,%34,%35,%36,%37,%38,%39}, da, db, p, 1, 1, 1, 0;\n}\n"
template <bool FIRST>
__device__ __forceinline__ void wgmma80(float (&d)[40], uint32_t alo, uint32_t blo_) {
    if (FIRST) asm volatile(GK_WGMMA("0") : GK_ACC("=f") : "r"(alo), "r"(blo_), "r"(DESC_HI));
    else       asm volatile(GK_WGMMA("1") : GK_ACC("+f") : "r"(alo), "r"(blo_), "r"(DESC_HI));
}
template <int KQ>
__device__ __forceinline__ void gemm_quarter(float (&d)[40], uint32_t unit, uint32_t tile, uint32_t bar, uint32_t parity, uint32_t rel = 0) {
    mbar_wait(bar + KQ * 8, parity);
    __syncwarp();
    const uint32_t a = desc_lo(unit), b = desc_lo(tile) + ((KQ * KB) >> 4);
    wg_fence();
    wgmma80<KQ == 0>(d, a, b);
    if (KQ) { wg_commit(); wg_wait<1>(); warp_arrive(rel); }
    wgmma80<false>(d, a + 128, b + 2);
    wgmma80<false>(d, a + 256, b + 4);
    wgmma80<false>(d, a + 384, b + 6);
    wg_commit();
}
__device__ __forceinline__ void stsm4t(uint32_t a, uint32_t r0, uint32_t r1, uint32_t r2, uint32_t r3) {
    asm volatile("stmatrix.sync.aligned.m8n8.x4.trans.shared.b16 [%0], {%1,%2,%3,%4};" :: "r"(a), "r"(r0), "r"(r1), "r"(r2), "r"(r3) : "memory");
}
__device__ __forceinline__ void stsm4(uint32_t a, uint32_t r0, uint32_t r1, uint32_t r2, uint32_t r3) {
    asm volatile("stmatrix.sync.aligned.m8n8.x4.shared.b16 [%0], {%1,%2,%3,%4};" :: "r"(a), "r"(r0), "r"(r1), "r"(r2), "r"(r3) : "memory");
}
__device__ __forceinline__ uint4 ldsm4(uint32_t a) {
    uint4 v; asm volatile("ldmatrix.sync.aligned.m8n8.x4.shared.b16 {%0,%1,%2,%3}, [%4];" : "=r"(v.x), "=r"(v.y), "=r"(v.z), "=r"(v.w) : "r"(a) : "memory"); return v;
}
__device__ __forceinline__ void mma16816(float (&c)[4], uint32_t a0, uint32_t a1, uint32_t a2, uint32_t a3, uint32_t b0, uint32_t b1) {
    asm volatile("mma.sync.aligned.m16n8k16.row.col.f32.bf16.bf16.f32 {%0,%1,%2,%3}, {%4,%5,%6,%7}, {%8,%9}, {%0,%1,%2,%3};"
        : "+f"(c[0]), "+f"(c[1]), "+f"(c[2]), "+f"(c[3]) : "r"(a0), "r"(a1), "r"(a2), "r"(a3), "r"(b0), "r"(b1));
}
__device__ __forceinline__ void pack_acc(uint32_t (&h)[20], const float (&d)[40]) {
#pragma unroll
    for (int i = 0; i < 20; ++i) h[i] = pack_bf16(d[2 * i], d[2 * i + 1]);
}
__device__ __forceinline__ void store_tile(const uint32_t (&h)[20], uint32_t tile, int mt, int w4, int lane) {
    const int r = lane & 7;
    const uint32_t base = tile + mt * KB + (((lane >> 4) * 8 + r) * 128) + (((2 * w4 + ((lane >> 3) & 1)) ^ r) << 4);
#pragma unroll
    for (int i = 0; i < 5; ++i) stsm4t(base + i * 2048, h[4 * i], h[4 * i + 1], h[4 * i + 2], h[4 * i + 3]);
}
__device__ __forceinline__ void fma8(float (&a)[8], float w, const uint4& v) {
    a[0] = fmaf(w, blo(v.x), a[0]); a[1] = fmaf(w, bhi(v.x), a[1]);
    a[2] = fmaf(w, blo(v.y), a[2]); a[3] = fmaf(w, bhi(v.y), a[3]);
    a[4] = fmaf(w, blo(v.z), a[4]); a[5] = fmaf(w, bhi(v.z), a[5]);
    a[6] = fmaf(w, blo(v.w), a[6]); a[7] = fmaf(w, bhi(v.w), a[7]);
}
__device__ __forceinline__ float dot8(const float (&q)[8], const uint4& v) {
    float s = q[0] * blo(v.x);
    s = fmaf(q[1], bhi(v.x), s); s = fmaf(q[2], blo(v.y), s); s = fmaf(q[3], bhi(v.y), s);
    s = fmaf(q[4], blo(v.z), s); s = fmaf(q[5], bhi(v.z), s); s = fmaf(q[6], blo(v.w), s); s = fmaf(q[7], bhi(v.w), s);
    return s;
}
__device__ __forceinline__ uint4 pack8(const float (&a)[8], float s) {
    return make_uint4(pack_bf16(a[0] * s, a[1] * s), pack_bf16(a[2] * s, a[3] * s), pack_bf16(a[4] * s, a[5] * s), pack_bf16(a[6] * s, a[7] * s));
}
__device__ __forceinline__ uint32_t hmul2(uint32_t a, uint32_t b) { uint32_t d; asm("mul.rn.bf16x2 %0, %1, %2;" : "=r"(d) : "r"(a), "r"(b)); return d; }
__device__ __forceinline__ uint32_t tile_chunk(uint32_t tile, int r, int c) {
    return tile + (c >> 3) * KB + r * 128 + (((c & 7) ^ (r & 7)) << 4);
}
__device__ __forceinline__ uint32_t wsum4(const uint32_t (&a)[4], uint32_t r0, uint32_t r1, uint32_t r2, uint32_t r3) {
    uint32_t z;
    asm("{\n.reg .b32 t;\nmul.rn.bf16x2 t, %1, %5;\nfma.rn.bf16x2 t, %2, %6, t;\nfma.rn.bf16x2 t, %3, %7, t;\nfma.rn.bf16x2 %0, %4, %8, t;\n}"
        : "=r"(z) : "r"(a[0]), "r"(a[1]), "r"(a[2]), "r"(a[3]), "r"(r0), "r"(r1), "r"(r2), "r"(r3));
    return z;
}
__device__ __forceinline__ void softmax4(const float (&s)[4], const float (&u)[4], int lane, uint32_t (&a)[4]) {
    const bool b = lane & 4, c = lane & 8;
    const float k0 = (b ? u[1] : s[0]) + __shfl_xor_sync(0xffffffffu, b ? s[1] : u[0], 4);
    const float k1 = (b ? u[3] : s[2]) + __shfl_xor_sync(0xffffffffu, b ? s[3] : u[2], 4);
    const float e = (c ? k1 : k0) + __shfl_xor_sync(0xffffffffu, c ? k0 : k1, 9);
    float pe;
    asm("ex2.approx.ftz.f32 %0, %1;" : "=f"(pe) : "f"(e * (0.0625f * 1.4426950408889634f)));
    const int l0 = (lane >> 4) * 18;
    const float p0 = __shfl_sync(0xffffffffu, pe, l0), p1 = __shfl_sync(0xffffffffu, pe, l0 + 9);
    const float p2 = __shfl_sync(0xffffffffu, pe, l0 + 4), p3 = __shfl_sync(0xffffffffu, pe, l0 + 13);
    float inv;
    asm("rcp.approx.ftz.f32 %0, %1;" : "=f"(inv) : "f"(((p0 + p1) + (p2 + p3)) + 1e-9f));
    a[0] = pack_bf16(p0 * inv, p0 * inv); a[1] = pack_bf16(p1 * inv, p1 * inv);
    a[2] = pack_bf16(p2 * inv, p2 * inv); a[3] = pack_bf16(p3 * inv, p3 * inv);
}
__device__ __forceinline__ void attention_chunks(const uint4 (&r)[4][2], uint32_t tile, int node, int lane) {
    const uint32_t qa = tile_chunk(tile, node + (lane >> 4), lane & 15);
    const uint4 q0 = lds128(qa), q1 = lds128(qa + 2 * KB);
    float s[4] = {0.f, 0.f, 0.f, 0.f}, u[4] = {0.f, 0.f, 0.f, 0.f};
    mma16816(s, r[0][0].x, r[1][0].x, r[0][0].y, r[1][0].y, q0.x, q0.y); mma16816(u, r[2][0].x, r[3][0].x, r[2][0].y, r[3][0].y, q0.x, q0.y);
    mma16816(s, r[0][0].z, r[1][0].z, r[0][0].w, r[1][0].w, q0.z, q0.w); mma16816(u, r[2][0].z, r[3][0].z, r[2][0].w, r[3][0].w, q0.z, q0.w);
    mma16816(s, r[0][1].x, r[1][1].x, r[0][1].y, r[1][1].y, q1.x, q1.y); mma16816(u, r[2][1].x, r[3][1].x, r[2][1].y, r[3][1].y, q1.x, q1.y);
    mma16816(s, r[0][1].z, r[1][1].z, r[0][1].w, r[1][1].w, q1.z, q1.w); mma16816(u, r[2][1].z, r[3][1].z, r[2][1].w, r[3][1].w, q1.z, q1.w);
    uint32_t a[4];
    softmax4(s, u, lane, a);
#pragma unroll
    for (int h = 0; h < 2; ++h)
        sts128(qa + h * 2 * KB, make_uint4(wsum4(a, r[0][h].x, r[1][h].x, r[2][h].x, r[3][h].x), wsum4(a, r[0][h].y, r[1][h].y, r[2][h].y, r[3][h].y),
                                           wsum4(a, r[0][h].z, r[1][h].z, r[2][h].z, r[3][h].z), wsum4(a, r[0][h].w, r[1][h].w, r[2][h].w, r[3][h].w)));
}
__device__ __forceinline__ void attention_frags(const uint4 (&r)[2][4], uint32_t tile, int node, int lane) {
    const int nd = node + ((lane >> 2) & 1);
    const uint32_t qa = tile + (lane >> 4) * KB + nd * 128 + (((lane ^ (lane >> 1 & 4) ^ nd) & 7) << 4);
    const uint4 q0 = ldsm4(qa), q1 = ldsm4(qa + 2 * KB);
    float s[4] = {0.f, 0.f, 0.f, 0.f}, u[4] = {0.f, 0.f, 0.f, 0.f};
    mma16816(s, r[0][0].x, r[0][0].y, r[0][0].z, r[0][0].w, q0.x, q0.y); mma16816(u, r[1][0].x, r[1][0].y, r[1][0].z, r[1][0].w, q0.x, q0.y);
    mma16816(s, r[0][1].x, r[0][1].y, r[0][1].z, r[0][1].w, q0.z, q0.w); mma16816(u, r[1][1].x, r[1][1].y, r[1][1].z, r[1][1].w, q0.z, q0.w);
    mma16816(s, r[0][2].x, r[0][2].y, r[0][2].z, r[0][2].w, q1.x, q1.y); mma16816(u, r[1][2].x, r[1][2].y, r[1][2].z, r[1][2].w, q1.x, q1.y);
    mma16816(s, r[0][3].x, r[0][3].y, r[0][3].z, r[0][3].w, q1.z, q1.w); mma16816(u, r[1][3].x, r[1][3].y, r[1][3].z, r[1][3].w, q1.z, q1.w);
    uint32_t a[4];
    softmax4(s, u, lane, a);
#pragma unroll
    for (int h = 0; h < 2; ++h)
        stsm4(qa + h * 2 * KB, wsum4(a, r[0][2 * h].x, r[0][2 * h].y, r[1][2 * h].x, r[1][2 * h].y), wsum4(a, r[0][2 * h].z, r[0][2 * h].w, r[1][2 * h].z, r[1][2 * h].w),
              wsum4(a, r[0][2 * h + 1].x, r[0][2 * h + 1].y, r[1][2 * h + 1].x, r[1][2 * h + 1].y), wsum4(a, r[0][2 * h + 1].z, r[0][2 * h + 1].w, r[1][2 * h + 1].z, r[1][2 * h + 1].w));
}
__device__ __noinline__ void attention_generic(const Params& p, uint32_t tile, int nl, int node, int lane) {
    const uint32_t qa = tile_chunk(tile, nl, lane);
    const uint4 qv = lds128(qa);
    const float q[8] = {blo(qv.x), bhi(qv.x), blo(qv.y), bhi(qv.y), blo(qv.z), bhi(qv.z), blo(qv.w), bhi(qv.w)};
    float z[8] = {0.f, 0.f, 0.f, 0.f, 0.f, 0.f, 0.f, 0.f};
    float den = 0.f;
#pragma unroll 1
    for (int e = 0; e < p.Ee; e += 32) {
        const bool m = (e + lane < p.Ee) && (__ldg(p.edst + e + lane) == node);
        const int sv = m ? __ldg(p.esrc + e + lane) : 0;
        uint32_t bal = __ballot_sync(0xffffffffu, m);
        while (bal) {
            const int l = __ffs(bal) - 1; bal &= bal - 1;
            const uint4 v = ldg_in(row_ptr(p.x + lane * 16, __shfl_sync(0xffffffffu, sv, l)));
            float c = dot8(q, v);
#pragma unroll
            for (int o = 16; o; o >>= 1) c += __shfl_xor_sync(0xffffffffu, c, o);
            const float pe = expf(c * 0.0625f);
            den += pe;
            fma8(z, pe, v);
        }
    }
    sts128(qa, pack8(z, 1.f / (den + 1e-9f)));
}
__device__ __noinline__ void local_generic(const Params& p, int node0, int w, int lane) {
    float a0[8], a1[8], a2[8], a3[8];
#pragma unroll
    for (int k = 0; k < 8; ++k) { a0[k] = 0.f; a1[k] = 0.f; a2[k] = 0.f; a3[k] = 0.f; }
#pragma unroll 1
    for (int e = 0; e < p.E; e += 32) {
        const int dl = (e + lane < p.E) ? __ldg(p.dst + e + lane) - node0 - w : -1;
        const int k = dl == 0 ? 0 : dl == AW ? 1 : dl == 2 * AW ? 2 : (dl == 3 * AW && w + 3 * AW < NPC) ? 3 : -1;
        const int sv = k >= 0 ? __ldg(p.src + e + lane) : 0;
        uint32_t bal = __ballot_sync(0xffffffffu, k >= 0);
        while (bal) {
            const int l = __ffs(bal) - 1; bal &= bal - 1;
            const int s = __shfl_sync(0xffffffffu, sv, l), kk = __shfl_sync(0xffffffffu, k, l);
            const uint4 v = ldg_sc(p.H + lane * N + s);
            if (kk & 2) { if (kk & 1) fma8(a3, 1.f, v); else fma8(a2, 1.f, v); }
            else        { if (kk & 1) fma8(a1, 1.f, v); else fma8(a0, 1.f, v); }
        }
    }
    const int n = node0 + w;
    red_row(p.out + n * 32 + lane, pack8(a0, __bfloat162float(p.dis[n])));
    red_row(p.out + (n + AW) * 32 + lane, pack8(a1, __bfloat162float(p.dis[n + AW])));
    red_row(p.out + (n + 2 * AW) * 32 + lane, pack8(a2, __bfloat162float(p.dis[n + 2 * AW])));
    if (w + 3 * AW < NPC) red_row(p.out + (n + 3 * AW) * 32 + lane, pack8(a3, __bfloat162float(p.dis[n + 3 * AW])));
}
__device__ __forceinline__ uint32_t hadd2(uint32_t a, uint32_t b) { uint32_t d; asm("add.rn.bf16x2 %0, %1, %2;" : "=r"(d) : "r"(a), "r"(b)); return d; }
__device__ __forceinline__ float plo(uint32_t v) { uint32_t d; asm("prmt.b32 %0, %1, 0, 0x1044;" : "=r"(d) : "r"(v)); return __uint_as_float(d); }
template <int HI, int NR>
__device__ __forceinline__ uint32_t agg_sum(uint32_t w, uint32_t base) {
    uint32_t a, r0, r1, r2, r3;
    if (HI) asm("dp2a.hi.u32.u32 %0, %1, %2, %3;" : "=r"(a) : "r"(w), "r"(0x10000010u), "r"(base));
    else    asm("dp2a.lo.u32.u32 %0, %1, %2, %3;" : "=r"(a) : "r"(w), "r"(0x10000010u), "r"(base));
    if (NR == 2) {
        asm volatile("ldmatrix.sync.aligned.m8n8.x2.shared.b16 {%0,%1}, [%2];" : "=r"(r0), "=r"(r1) : "r"(a));
        return hadd2(r0, r1);
    }
    asm volatile("ldmatrix.sync.aligned.m8n8.x4.shared.b16 {%0,%1,%2,%3}, [%4];" : "=r"(r0), "=r"(r1), "=r"(r2), "=r"(r3) : "r"(a));
    return hadd2(hadd2(r0, r1), hadd2(r2, r3));
}
struct Unit { uint4 a, b; };
__device__ __forceinline__ uint32_t unit_stale(const Unit& x, uint32_t lt) {
    if (CHK1) return ((x.a.x ^ lt) | (x.b.x ^ lt)) & 0xc000u;
    const uint32_t o = x.a.x | x.a.y | x.a.z | x.a.w | x.b.x | x.b.y | x.b.z | x.b.w, a = x.a.x & x.a.y & x.a.z & x.a.w & x.b.x & x.b.y & x.b.z & x.b.w;
    return ((o ^ lt) | (a ^ lt)) & 0xc000u;
}
__device__ __forceinline__ uint32_t agg_tail(float lo, float hi, uint32_t s, const uint4& w, uint32_t base, uint32_t b5, uint32_t b6) {
    if (b5 > 0xffffu) {
        s = hadd2(s, agg_sum<1, 4>(w.z, base));
        if (b6) {
            const uint32_t u = b6 > 0xffffu ? agg_sum<0, 4>(w.w, base) : agg_sum<0, 2>(w.w, base);
            lo += plo(u); hi += bhi(u);
        }
    } else if (b5) s = hadd2(s, agg_sum<1, 2>(w.z, base));
    const float f = bhi(w.w);
    return pack_bf16((lo + plo(s)) * f, (hi + bhi(s)) * f);
}
__device__ __forceinline__ void agg_unit(const Unit& x, uint32_t base, uint32_t stg, uint32_t lt) {
    const uint32_t s0 = hadd2(agg_sum<0, 4>(x.a.x, base), agg_sum<1, 4>(x.a.x, base)), u0 = hadd2(agg_sum<0, 4>(x.b.x, base), agg_sum<1, 4>(x.b.x, base));
    const uint32_t s1 = hadd2(agg_sum<0, 4>(x.a.y, base), agg_sum<1, 4>(x.a.y, base)), u1 = hadd2(agg_sum<0, 4>(x.b.y, base), agg_sum<1, 4>(x.b.y, base));
    const uint32_t s2 = agg_sum<0, 4>(x.a.z, base), u2 = agg_sum<0, 4>(x.b.z, base);
    const uint32_t a5 = __ballot_sync(0xffffffffu, x.a.z > (lt | 0xffffu)), a6 = __ballot_sync(0xffffffffu, x.a.w & 0x3fffu);
    const uint32_t b5 = __ballot_sync(0xffffffffu, x.b.z > (lt | 0xffffu)), b6 = __ballot_sync(0xffffffffu, x.b.w & 0x3fffu);
    const uint32_t oa = agg_tail(plo(s0) + plo(s1), bhi(s0) + bhi(s1), s2, x.a, base, a5, a6);
    const uint32_t ob = agg_tail(plo(u0) + plo(u1), bhi(u0) + bhi(u1), u2, x.b, base, b5, b6);
    asm volatile("stmatrix.sync.aligned.m8n8.x2.shared.b16 [%0], {%1,%2};" :: "r"(stg), "r"(oa), "r"(ob) : "memory");
}

__global__ void __launch_bounds__(NTHR, 1)
fused_kernel(const __grid_constant__ Params p,
             const __grid_constant__ CUtensorMap tmX, const __grid_constant__ CUtensorMap tmWl,
             const __grid_constant__ CUtensorMap tmM, const __grid_constant__ CUtensorMap tmWv,
             const __grid_constant__ CUtensorMap tmR, const __grid_constant__ CUtensorMap tmO,
             const __grid_constant__ CUtensorMap tmG, const __grid_constant__ CUtensorMap tmQ,
             const __grid_constant__ CUtensorMap tmK, const __grid_constant__ CUtensorMap tmV3)
{
    extern __shared__ __align__(1024) unsigned char smem[];
    const uint32_t sb = s32(smem);
    const int tid = threadIdx.x, lane = tid & 31;
    const int warp = __shfl_sync(0xffffffffu, tid >> 5, 0);
    const int cta = blockIdx.x;
    const int node0 = cta * NPC;
    const bool rowcta = cta < RCTA;
    const int slice = cta >> 2, quarter = cta & 3;
    const int nlast = 12 + (quarter == 3);
    const int i0 = (cta >> 3) * 16, j0 = (cta & 7) * 32;
    const uint32_t bars = sb + SM_MISC;
    const uint32_t sS = sb + SM_S, sT = sb + SM_T;

    const bool stage = rowcta && !p.force_eslow;
    auto slow_cta = [&]() { uint32_t a, b; asm volatile("ld.shared.v2.u32 {%0, %1}, [%2];" : "=r"(a), "=r"(b) : "r"(bars + MI_SLOW) : "memory"); return a || b > OVCAP; };
    auto publish = [&](int set) {
        const uint4 dv = lds128(bars + MI_DIS + set * 16);
        uint4 v = lds128(sb + X_IMG + set * 512 + lane * 16);
        const uint4 z = lds128(sb + X_DEF + set * 64 + (lane & 3) * 16);
        if ((lane & 3) == 3) { v.x = __byte_perm(v.x, v.y, 0x5410); v.y = v.w; }
        v.x = __vmaxu2(v.x, z.x); v.y = __vmaxu2(v.y, z.y); v.z = __vmaxu2(v.z, z.z); v.w = __vmaxu2(v.w, z.w);
        if (slow_cta()) v = make_uint4(0, 0, 0, 0);
        const uint32_t lt = list_tag(lds32(bars + MI_EPOCH));
        v.x |= lt; v.y |= lt; v.z |= lt; v.w |= lt;
        if ((lane & 3) == 3) { const uint32_t sel = lane & 16 ? 0x7632 : 0x5410; v.z = __byte_perm(dv.x, dv.y, sel); v.w = __byte_perm(dv.z, dv.w, sel); }
        uint32_t* ip = (uint32_t*)p.idx + (cta * 10 + set) * 128 + lane;
        st_relaxed(ip, __byte_perm(v.x, v.z, 0x5410));      st_relaxed(ip + 32, __byte_perm(v.x, v.z, 0x7632));
        st_relaxed(ip + 64, __byte_perm(v.y, v.w, 0x5410)); st_relaxed(ip + 96, __byte_perm(v.y, v.w, 0x7632));
    };

    if (warp >= AW) {
        const int pw = warp - AW;
        if (elect()) {
            auto init = [&](int b0, int b1, int c) {
#pragma unroll
                for (int b = b0; b < b1; b += 8) mbar_init(bars + b, c);
            };
            if (pw == 0)      { PROF(0); prefetch_map(&tmQ); prefetch_map(&tmK); prefetch_map(&tmX); prefetch_map(&tmWl); init(B_K, B_A, 1); }
            else if (pw == 1) { init(B_A, B_F, 4); mbar_init(bars + B_S, 6); mbar_init(bars + B_VE, GW); mbar_init(bars + B_Z, AW); init(B_HV, B_RV + 8, 1); }
            else if (pw == 2) { init(B_F, B_GO, GW); init(B_FA, B_SENT, 8); mbar_init(bars + B_SENT, LW + 4); }
            else              { init(B_GO, B_Z, 1); init(B_RND, B_RND + 96, 12); mbar_init(bars + B_RND + 96, nlast); }
            asm volatile("fence.mbarrier_init.release.cluster;" ::: "memory");
        }
        bar_arrive(4, LT + 128);
        if (pw) bar_sync(0, GT + 128); else bar_arrive(0, GT + 128);
        auto load_units = [&](const CUtensorMap* tm, int kq, int slot) {
            if (elect()) { mbar_expect(bars + B_K + kq * 8, 4 * UNIT); tma3d(sS + slot * UNIT, tm, kq * 64, bars + B_K + kq * 8); }
        };
        const int v0 = pw ? pw - 2 : 2;
        auto tile_rows = [&](uint2 (&e)[6], int c) {
#pragma unroll
            for (int n = 0; n < 6; ++n) {
                const int v = min(v0 + 3 * n, 15);
                asm volatile("ld.shared.v2.u32 {%0, %1}, [%2];" : "=r"(e[n].x), "=r"(e[n].y) : "r"(bars + MI_ES + ((v >> 2) * 16 + c * 4 + (v & 3)) * 8) : "memory");
            }
        };
        auto stage_tiles = [&](const uint2 (&e)[6], int c) {
            mbar_wait(bars + (c ? B_F + 32 + c * 8 : T0BAR), 0);
            if (elect()) {
#pragma unroll
                for (int n = 0; n < 6; ++n) {
                    const int v = v0 + 3 * n;
                    if (n < 5 || v < 16) {
                        const uint32_t dst = sS + (A_TILES >> (8 * c) & 255) * UNIT + v * 2048, bar = bars + B_A + ((v & 12) + c) * 8;
                        mbar_expect(bar, 2048);
                        tma2d(dst, &tmG, 0, e[n].x & 0xffffu, bar);        tma2d(dst + 512, &tmG, 0, e[n].x >> 16, bar);
                        tma2d(dst + 1024, &tmG, 0, e[n].y & 0xffffu, bar); tma2d(dst + 1536, &tmG, 0, e[n].y >> 16, bar);
                    }
                }
            }
            if (pw == 2 && lane == 0) PROF(45 + c);
        };
        if (pw == 0) {
            if (elect()) {
                mbar_expect(bars + B_QK, 3 * UNIT);
                tma3d(sS + A3 * UNIT, &tmQ, i0, bars + B_QK);
                tma3d(sS + (A3 + 1) * UNIT, &tmK, j0, bars + B_QK);
                if (rowcta) {
#pragma unroll
                    for (int kq = 0; kq < 4; ++kq) mbar_expect(bars + B_K + kq * 8, KB + 4 * UNIT);
#pragma unroll
                    for (int i = 7; i >= 0; --i) {
                        const int kq = (XORD >> (4 * i)) & 3;
                        if ((XORD >> (4 * i)) & 4) tma3d(sS + (kq == 3 ? A4 : 4 * kq) * UNIT, &tmWl, kq * 64, bars + B_K + kq * 8);
                        else tma2d(sT + kq * KB, &tmX, kq * 64, node0, bars + B_K + kq * 8);
                    }
                    PROF(3);
                    prefetch_map(&tmM); prefetch_map(&tmG); prefetch_map(&tmWv); prefetch_map(&tmV3); prefetch_map(&tmR);
                }
            }
        }
        if (pw >= 2 && stage) {
            const uint4 e = ldg_in(p.esrc + (node0 + 32 * (pw - 2) + lane) * 4);
            asm volatile("st.shared.v2.u32 [%0], {%1, %2};" :: "r"(bars + MI_ES + ((pw - 2) * 32 + lane) * 8), "r"(e.x | e.y << 16), "r"(e.z | e.w << 16) : "memory");
        }
        if (pw == 1 && rowcta && lane < 10) sts128(bars + MI_DIS + lane * 16, ldg_in(p.dis + node0 + lane * 8));
        {
            bar_sync(1, GT + 128);
            const int v = tid - AW * 32;
            const float* rp = (const float*)(smem + SM_X) + (v >> 3) * 32 + (((v & 7) * 4 + (v & 24)) & 31);
            const float4 v0 = *(const float4*)rp, v1 = *(const float4*)(rp + 512), v2 = *(const float4*)(rp + 1024), v3 = *(const float4*)(rp + 1536);
            p.M[(i0 + (v >> 3)) * 64 + (j0 >> 2) + (v & 7)] =
                make_uint2(pack_bf16((v0.x + v1.x) + (v2.x + v3.x), (v0.y + v1.y) + (v2.y + v3.y)),
                           pack_bf16((v0.z + v1.z) + (v2.z + v3.z), (v0.w + v1.w) + (v2.w + v3.w)));
            warp_arrive(bars + B_SENT);
        }
        if (pw != 1 && rowcta) {
            uint2 e[4][6];
#pragma unroll
            for (int c = 0; c < 4 - G3; ++c) tile_rows(e[c], c);
            mbar_wait(bars + B_EPO, 0);
            mbar_wait(bars + B_F, 0);
#pragma unroll 1
            for (int c = 0; c < 4 - G3; ++c) {
                if (pw == 0 && c == 0) {
                    mbar_wait(bars + B_CGO, 0);
                    wait_count(p.sync + SY_M, (lds32(bars + MI_EPOCH) + 1) * NCTA);
                    fence_async_gmem();
                    if (lane == 0) PROF(2);
                    load_units(&tmM, 0, A0);
                    if (lane == 0) PROF(39);
                    mbar_wait(bars + B_F + 8, 0);  load_units(&tmM, 1, A1);
                    mbar_wait(bars + B_F + 16, 0); load_units(&tmM, 2, A2);
                    warp_arrive(bars + B_MI);
                    if (lane == 0) PROF(40);
                }
                if (pw == 0 && c == 1) { mbar_wait(bars + B_F + 32, 0); load_units(&tmM, 3, A0); }
                if (stage) stage_tiles(e[0], c);
#pragma unroll
                for (int n = 0; n < 6; ++n) { e[0][n] = e[1][n]; e[1][n] = e[2][n]; if (!G3) e[2][n] = e[3][n]; }
            }
        }
        if (pw == 0) {
            if (rowcta) {
                if (HRW == 1) mbar_wait(bars + B_HR, 0);
                mbar_wait(bars + B_FA, 0);      fence_async_smem();  load_units(&tmWv, 0, A3);
                if (HRW == 2) mbar_wait(bars + B_HR, 0);
                mbar_wait(bars + B_FA + 8, 0);  fence_async_smem();  load_units(&tmWv, 1, A1);
                mbar_wait(bars + B_FA + 16, 0); fence_async_smem();  load_units(&tmWv, 2, A2);
                mbar_wait(bars + B_HR, 0);
                mbar_wait(bars + B_XF, 0);      fence_async_smem();
                if (elect()) {
                    mbar_expect(bars + B_K + 24, 4 * UNIT);
#pragma unroll
                    for (int ks = 0; ks < 4; ++ks) tma3d(sS + (A5 + ks) * UNIT, &tmV3, 192 + ks * 16, bars + B_K + 24);
                }
                if (lane == 0) PROF(5);
            }
        } else if (pw == 1) {
            mbar_wait(bars + B_SENT, 0);
            if (elect()) { PROF(38); red_release(p.sync + SY_M); PROF(1); mbar_arrive(bars + B_CGO); }
            if (VPF && lane < 8) asm volatile("prefetch.global.L2 [%0];" :: "l"(p.wv + (cta * 8 + lane) * 128));
            mbar_wait(bars + B_EPO, 0);
            if (rowcta) {
                mbar_wait(bars + B_HS, 0);
                mbar_wait(bars + B_LF, 0);
                fence_async_smem();
                mbar_wait(bars + B_MI, 0);
                if (HGATE >= 0) mbar_wait(bars + B_K + HGATE * 8, 1);
                uint32_t tn = clk();
#pragma unroll 1
                for (int s = 0; s < 32; s += 2) {
                    wait_clk(tn); tn += HPER;
                    if (elect()) {
                        bulk_store(p.H + s * N + node0, sS + A4 * UNIT + s * 1280, 1280);
                        bulk_store(p.H + (s + 1) * N + node0, sS + A4 * UNIT + s * 1280 + 1280, 1280);
                    }
                }
#pragma unroll 1
                for (int z = cta; z < ER * AW * 16; z += RCTA) {
                    wait_clk(tn); tn += HPER;
                    if (elect()) bulk_store(p.out + ((z & 3) * (UPQ * 16) + (z >> 2) * 4) * 32, sb + X_ZERO, 2048);
                }
                if (elect()) {
                    bulk_commit();
                    asm volatile("cp.async.bulk.wait_group 0;" ::: "memory");
                    PROF(43);
                    fence_async_gmem();
                    red_release(p.sync + SY_H);
                    mbar_arrive(bars + B_HR);
                    PROF(31);
                }
            }
            wait_count(p.sync + SY_H, (lds32(bars + MI_EPOCH) + 1) * RCTA);
            fence_async_gmem();
            warp_arrive(bars + B_HV);
            if (lane == 0) PROF(6);
            const char* hs = (const char*)(p.H + slice * N) - 128;
            auto chunk = [&](int bar, int lo, int hi) {
                if (rowcta && bar) mbar_wait(bars + bar, 0);
                if (bar >= B_FA) fence_async_smem();
                if (lo == 128) { if (lane < 8) sts128(sS + lane * 16, make_uint4(0, 0, 0, 0)); __syncwarp(); }
                if (elect()) { mbar_expect(bars + B_S, hi - lo); bulk_load(sS + lo, hs + lo, hi - lo, bars + B_S); }
            };
            chunk(0, A4 * UNIT, A5 * UNIT);
            chunk(B_FA + 24, 128, 4 * UNIT);
            chunk(B_F + 64, A3 * UNIT, (A3 + 4) * UNIT);
            chunk(B_F + 72, A1 * UNIT, (A1 + 4) * UNIT);
            chunk(B_F + 80, A2 * UNIT, (A2 + 4) * UNIT);
            chunk(B_F + 88, A5 * UNIT, SLICE_END);
            if (lane == 0) PROF(7);
        } else {
            mbar_wait(bars + B_EPO, 0);
            const uint32_t epoch1 = lds32(bars + MI_EPOCH) + 1;
            if (pw == 2) {
                if (rowcta) {
                    uint32_t early = 0;
#pragma unroll
                    for (int r = 0; r < 5; ++r) { const int u = cta * 5 + r; early |= (u - min(u / UPQ, 3) * UPQ < ER * AW) << r; }
                    auto put_r = [&](bool add) {
#pragma unroll 1
                        for (int r = 0; r < 5; ++r) {
                            const int u = cta * 5 + r;
                            if ((early >> r & 1) == add) {
                                if (elect()) {
#pragma unroll
                                    for (int kb = 0; kb < 4; ++kb) {
                                        if (add) tma2d_add(&tmR, sT + kb * KB + r * 2048, kb * 64, u * 16);
                                        else     tma2d_store(&tmR, sT + kb * KB + r * 2048, kb * 64, u * 16);
                                    }
                                }
                                if (RPER && add) wait_clk(clk() + RPER);
                            }
                        }
                        bulk_commit();
                    };
                    mbar_wait(bars + B_R, 0);
                    fence_async_smem();
                    put_r(false);
                    if (elect()) {
                        asm volatile("cp.async.bulk.wait_group 0;" ::: "memory");
                        fence_async_gmem();
                        p.sync[SY_SLOW + cta] = slow_cta();
                        red_release(p.sync + SY_R);
                        PROF(22);
                    }
                    mbar_wait(bars + B_S, 0);
                    put_r(true);
                    bulk_wait_read<0>();
                    if (lane == 0) PROF(41);
                }
                warp_arrive(bars + B_TF);
                wait_count(p.sync + SY_R, epoch1 * RCTA);
                fence_async_gmem();
                warp_arrive(bars + B_RV);
                if (lane == 0) PROF(23);
            } else {
                if (lane == 0) prefetch_map(&tmO);
                mbar_wait(bars + B_XF, 0);
                if (elect()) red_relaxed(p.sync + SY_L);
                wait_count(p.sync + SY_L, epoch1 * NCTA);
                warp_arrive(bars + B_GO);
                if (lane == 0) PROF(42);
                if (cta == 0 && lane < 16) *(volatile uint32_t*)(p.sync + lane * 32) = epoch1;
#pragma unroll 1
                for (int i = 0; i < 13; ++i) {
                    if (i == 2 * ER) mbar_wait(bars + B_RV, 0);
                    mbar_wait(bars + B_RND + i * 8, 0);
                    fence_async_smem();
                    if (elect()) {
                        tma2d_add(&tmO, sb + SM_X + i * 3072, slice * 8, quarter * (UPQ * 16) + i * 192);
                        if (i == 12 && quarter == 3) tma2d_add(&tmO, sb + SM_X + 13 * 3072, slice * 8, 3 * (UPQ * 16) + 13 * 192);
                    }
                    if (lane == 0 && !(i & 1)) PROF(53 + (i >> 1));
                }
                bulk_commit();
                if (lane == 0) PROF(8);
                bulk_wait_read<0>();
                if (lane == 0) PROF(9);
            }
        }
        if (pw < 2) {
            mbar_wait(bars + B_EPO, 0);
            mbar_wait(bars + B_XF, 0);
            const int novf = min(lds32(bars + MI_NOVF), (uint32_t)OVCAP);
#pragma unroll 1
            for (int o = 12 * pw; o < novf; o += 24) {
                const int n = novf - o;
                const uint32_t w = lds32(bars + MI_OVF + (o + min(lane, n - 1)) * 4);
                const uint32_t f = __ldg((const unsigned short*)p.dis + (w >> 14)) * 0x10001u;
                mbar_wait(bars + B_HV, 0);
                uint4 v[12];
#pragma unroll
                for (int i = 0; i < 12; i += 3) {
                    if (i < n) {
#pragma unroll
                        for (int j = i; j < i + 3; ++j) {
                            const uint32_t s = __shfl_sync(0xffffffffu, w, j) & 0x3fffu;
                            v[j] = make_uint4(0, 0, 0, 0);
                            if (j < n) v[j] = ldg_sc(p.H + lane * N + s);
                        }
#pragma unroll
                        for (int j = i; j < i + 3; ++j) {
                            const uint32_t fj = __shfl_sync(0xffffffffu, f, j);
                            v[j] = make_uint4(hmul2(v[j].x, fj), hmul2(v[j].y, fj), hmul2(v[j].z, fj), hmul2(v[j].w, fj));
                        }
                    }
                }
                mbar_wait(bars + B_RV, 0);
                const uint32_t go = __ballot_sync(0xffffffffu, lane < n && !ld_relaxed(p.sync + SY_SLOW + (w >> 14) / NPC));
#pragma unroll
                for (int j = 0; j < 12; ++j)
                    if (go >> j & 1) red_row(p.out + (__shfl_sync(0xffffffffu, w, j) >> 14) * 32 + lane, v[j]);
            }
            if (lane == 0) PROF(pw ? 48 : 44);
        }
    } else {
        const int g = lane >> 2, t = lane & 3;
        const int wi = warp < GW ? warp + LW : warp - GW;
        Unit x0, x1;
        const uint4* ip;
        auto fetch = [&](Unit& x, int j) { x.a = ld_relaxed4(ip + j * 64); x.b = ld_relaxed4(ip + j * 64 + 32); };
        auto fetch0 = [&]() { int l = lane; asm volatile("" : "+r"(l)); ip = p.idx + quarter * (UPQ * 64) + l; fetch(x0, wi); };
        if (warp < GW) {
            const int wg = warp >> 2, w4 = warp & 3;
            uint32_t h[20];
            if (rowcta) {
#pragma unroll
                for (int j = 0; j < 10; ++j) h[j] = __ldg((const uint32_t*)p.dis + (node0 >> 1) + 4 * j + t);
            }
            bar_sync(0, GT + 128);
            {
                float* red = (float*)(smem + SM_X);
                const int cw = (w4 - wg * (MW == 1 ? 1 : MW == 2 ? 2 : 0)) & 3;
                if (cw < MW) {
                    const uint32_t qa = sS + A3 * UNIT + wg * 2048 + (lane & 15) * 128 + (((lane >> 4) ^ (lane & 7)) << 4);
                    const uint32_t ka = sS + (A3 + 1) * UNIT + wg * 4096 + (cw * (32 / MW) + (lane & 7)) * 128 + (((lane >> 3) ^ (lane & 7)) << 4);
                    mbar_wait(bars + B_QK, 0);
                    __syncwarp();
                    if (tid == 0) PROF(33);
                    const uint4 a0 = ldsm4(qa), a1 = ldsm4(qa ^ 32), a2 = ldsm4(qa ^ 64), a3 = ldsm4(qa ^ 96);
                    uint4 bb[4 / MW][2];
#pragma unroll
                    for (int nb = 0; nb < 4 / MW; ++nb) { bb[nb][0] = ldsm4(ka + nb * 1024); bb[nb][1] = ldsm4((ka ^ 64) + nb * 1024); }
#pragma unroll
                    for (int nb = 0; nb < 4 / MW; ++nb) {
                        const uint4 b0 = bb[nb][0], b1 = bb[nb][1];
                        float c[4] = {0.f, 0.f, 0.f, 0.f}, e[4] = {0.f, 0.f, 0.f, 0.f};
                        mma16816(c, a0.x, a0.y, a0.z, a0.w, b0.x, b0.y); mma16816(e, a1.x, a1.y, a1.z, a1.w, b0.z, b0.w);
                        mma16816(c, a2.x, a2.y, a2.z, a2.w, b1.x, b1.y); mma16816(e, a3.x, a3.y, a3.z, a3.w, b1.z, b1.w);
                        float* rp = red + (wg * 16 + g) * 32 + (((cw * (4 / MW) + nb + g) & 3) * 8) + 2 * t;
                        *(float2*)rp         = make_float2(c[0] + e[0], c[1] + e[1]);
                        *(float2*)(rp + 256) = make_float2(c[2] + e[2], c[3] + e[3]);
                    }
                }
                bar_arrive(1, GT + 128);
            }
            if (rowcta) {
                float d[40];
                const uint32_t uw = sS + wg * UNIT, fb = bars + B_F;
                fence_async_smem();
                mbar_wait(bars + B_SENT, 0);
                if (tid == 0) PROF(35);
                gemm_quarter<0>(d, uw + A0 * UNIT, sT, bars + B_K, 0);
                if (tid == 0) PROF(10);
                gemm_quarter<1>(d, uw + A1 * UNIT, sT, bars + B_K, 0, fb);
                gemm_quarter<2>(d, uw + A2 * UNIT, sT, bars + B_K, 0, fb + 8);
                gemm_quarter<3>(d, uw + A4 * UNIT, sT, bars + B_K, 0, fb + 16);
                wg_wait<0>(); warp_arrive(fb + 24);
                if (tid == 0) PROF(11);
#pragma unroll
                for (int j = 9; j >= 0; --j) {
                    const float s0 = blo(h[j]), s1 = bhi(h[j]);
                    h[2 * j + 1] = pack_bf16(d[4 * j + 2] * s0, d[4 * j + 3] * s1);
                    h[2 * j]     = pack_bf16(d[4 * j] * s0, d[4 * j + 1] * s1);
                }
                mbar_wait(fb + 24, 0);
                __syncwarp();
                {
                    const uint32_t sa = sS + A4 * UNIT + warp * 2560 + (lane & 8) * 160 + (lane >> 4) * 128 + (lane & 7) * 16;
#pragma unroll
                    for (int i = 0; i < 5; ++i) stsm4t(sa + i * 256, h[4 * i], h[4 * i + 1], h[4 * i + 2], h[4 * i + 3]);
                }
                warp_arrive(bars + B_HS);
                if (QLF) mbar_wait(bars + B_LF, 0);
                uint4 e3 = make_uint4(0, 0, 0, 0);
                if (G3 && stage) e3 = ldg_in(p.esrc + (node0 + 16 * wg + 12 + w4) * 4);
                gemm_quarter<0>(d, uw + A0 * UNIT, sT, bars + B_K, 1);
                if (tid == 0) PROF(12);
                gemm_quarter<1>(d, uw + A1 * UNIT, sT, bars + B_K, 1, fb + 32);
                gemm_quarter<2>(d, uw + A2 * UNIT, sT, bars + B_K, 1, fb + 40);
                mbar_wait(bars + B_LF, 0);
                const uint32_t ebad = lds32(bars + MI_EBAD);
                gemm_quarter<3>(d, uw + A0 * UNIT, sT, bars + B_K, 1, fb + 48);
                if (tid == 0) PROF(13);
                wg_wait<0>(); warp_arrive(fb + 56);
                if (tid == 0) PROF(14);
                pack_acc(h, d);
                mbar_wait(fb + 32 + wg * 8, 0);
                __syncwarp();
                store_tile(h, sT, wg, w4, lane);
                warp_arrive(bars + B_Q);
                auto stage3 = [&]() {
                    mbar_wait(fb + 56, 0);
                    if (G3 && stage && elect()) {
                        const uint32_t dst = uw + A0 * UNIT + w4 * 2048, bar = bars + B_A + (4 * wg + 3) * 8;
                        mbar_expect(bar, 2048);
                        tma2d(dst, &tmG, 0, e3.x, bar);        tma2d(dst + 512, &tmG, 0, e3.y, bar);
                        tma2d(dst + 1024, &tmG, 0, e3.z, bar); tma2d(dst + 1536, &tmG, 0, e3.w, bar);
                    }
                };
                const uint32_t rows = uw + (w4 & 1) * 4096 + (lane & 4) * 512 + (lane & 8) * 64 + (((lane ^ (lane >> 2 & 4)) & 7) << 4);
#pragma unroll AUNR
                for (int c2 = 0; c2 < 4; c2 += 2) {
                    const int c = (w4 >> 1) + c2;
                    const int n = 16 * wg + 4 * c + 2 * (w4 & 1);
                    if (stage) mbar_wait(bars + B_A + (4 * wg + c) * 8, 0);
                    if (tid == 0) PROF(c ? 50 : 15);
                    if (tid == 96) PROF(c == 1 ? 51 : 52);
                    if (!ebad) {
                        const uint32_t ra = rows + (A_TILES >> (8 * c) & 255) * UNIT;
                        uint4 r[2][4];
#pragma unroll
                        for (int kb = 0; kb < 4; ++kb) { r[0][kb] = ldsm4(ra + kb * 128); r[1][kb] = ldsm4(ra + 1024 + kb * 128); }
                        warp_arrive(bars + B_FA + c * 8);
                        if (c2 == 0) { stage3(); mbar_wait(bars + B_Q, 0); }
                        __syncwarp();
                        attention_frags(r, sT, n, lane);
                    } else {
                        warp_arrive(bars + B_FA + c * 8);
                        if (c < 2) stage3();
                        mbar_wait(bars + B_Q, 0);
                        attention_generic(p, sT, n, node0 + n, lane); attention_generic(p, sT, n + 1, node0 + n + 1, lane);
                    }
                }
                fence_async_smem();
                warp_arrive(bars + B_Z);
                if (tid == 0) PROF(16);
                mbar_wait(bars + B_K, 0);
                if (tid == 0) PROF(17);
                gemm_quarter<0>(d, uw + A3 * UNIT, sT, bars + B_Z, 0);
                gemm_quarter<1>(d, uw + A1 * UNIT, sT, bars + B_K, 0, fb + 64);
                gemm_quarter<2>(d, uw + A2 * UNIT, sT, bars + B_K, 0, fb + 72);
                bool early = false;
                if (EFETCH == 1) { early = mbar_test(bars + B_GO, 0); if (early) fetch0(); }
                {
                    mbar_wait(bars + B_K + 24, 0);
                    __syncwarp();
                    const uint32_t a = desc_lo(sS + A5 * UNIT + wg * 2048), b = desc_lo(sT) + ((3 * KB) >> 4);
                    wg_fence();
                    wgmma80<false>(d, a, b);            wg_commit(); wg_wait<1>(); warp_arrive(fb + 80);
                    wgmma80<false>(d, a + 512, b + 2);  wg_commit(); wg_wait<1>(); warp_arrive(fb + 88);
                    if (EFETCH == 2) { early = mbar_test(bars + B_GO, 0); if (early) fetch0(); }
                    wgmma80<false>(d, a + 1024, b + 4);
                    wgmma80<false>(d, a + 1536, b + 6); wg_commit();
                    if (EFETCH == 3) { early = mbar_test(bars + B_GO, 0); if (early) fetch0(); }
                }
                wg_wait<0>(); warp_arrive(bars + B_VE);
                if (tid == 0) PROF(18);
                pack_acc(h, d);
                mbar_wait(wg == 3 ? bars + B_VE : fb + 64 + wg * 8, 0);
                __syncwarp();
                store_tile(h, sT, wg, w4, lane);
                warp_arrive(bars + B_R);
                if (!early) { mbar_wait(bars + B_GO, 0); fetch0(); }
                if (tid == 0) PROF(19);
            } else {
                mbar_wait(bars + B_GO, 0);
                fetch0();
            }
        } else {
            const int lw = warp - GW, tl = tid - GT;
            const uint32_t epoch = ld_relaxed(p.sync + (cta & 15) * 32);
            uint32_t dd[5], ss[5];
            {
                const int e0 = cta * p.chunk, e1 = min(e0 + p.chunk, p.Efast);
#pragma unroll
                for (int k = 0; k < 5; ++k) { dd[k] = (RCTA + (lane & 1)) * NPC; ss[k] = 0; }
#pragma unroll
                for (int k = 0; k < 2; ++k) {
                    const int e = e0 + 2 * (tl + k * LT);
                    if (e < e1) {
                        const int2 d = __ldg((const int2*)(p.dst + e)), s = __ldg((const int2*)(p.src + e));
                        dd[2 * k] = d.x; dd[2 * k + 1] = d.y; ss[2 * k] = s.x; ss[2 * k + 1] = s.y;
                    }
                }
                const int e = e0 + 4 * LT + tl;
                if (e < e1) { dd[4] = __ldg(p.dst + e); ss[4] = __ldg(p.src + e); }
            }
            int4 ed = make_int4(0, 0, 0, 0), es = make_int4(0, 0, 0, 0);
            if (stage) {
                if (tl < NPC) ed = __ldg((const int4*)p.edst + node0 + tl);
                es = __ldg((const int4*)p.esrc + node0 + 64 + 2 * lw + (lane >> 4));
            }
            {
                const uint32_t lo = (tl & 3) * 0x40004000u, hi = (NPC * 2 + (cta & 7)) * 0x010101u;
#pragma unroll
                for (int r = 0; r < 2; ++r) {
                    sts128(sb + X_OUT + (tl + r * LT) * 16, make_uint4(lo, lo, (lo & 0xffffu) | hi << 16, hi));
                    sts128(sb + X_IMG + (tl + r * LT) * 16, make_uint4(0, 0, 0, 0));
                }
            }
            if (tl < 32) sts128(bars + MI_PCNT + tl * 16, make_uint4(0, 0, 0, 0));
            if (tl == 32) { sts32(bars + MI_SLOW, p.force_slow); sts32(bars + MI_EBAD, p.force_eslow); sts32(bars + MI_NOVF, 0); sts32(bars + MI_FLAGS, 0); }
            bar_sync(2, LT);
            if (tl == 0) PROF(34);
            const int zero = lds32(bars + MI_PCNT + 127 * 4);
            uint32_t q[5], nx = 0, ox = 0;
            {
                uint32_t c[5];
#pragma unroll
                for (int k = 0; k < 5; ++k) {
                    dd[k] += zero;
                    c[k] = dd[k] / NPC;
                    q[k] = atoms_add(bars + MI_PCNT + c[k] * 4, c[k] < RCTA);
                }
                if (tl == 0) PROF(36);
#pragma unroll
                for (int k = 0; k < 5; ++k) {
                    const uint32_t w = (((dd[k] - c[k] * NPC) * 8 + (ss[k] & 7u)) << 14) + ss[k] + 8;
                    uint32_t sl = (q[k] >> 2) + (SROT ? (c[k] >> 3) & 3u : 0u);
                    if (SROT) sl = min(sl, sl - 5);
                    const uint32_t ca = sb + X_OUT + c[k] * 64 + ((q[k] + (c[k] >> 1)) & 3u) * 16 + sl;
                    if (q[k] < CELLN) { sts16(ca + sl, w); asm volatile("st.shared.u8 [%0 + 10], %1;" :: "r"(ca), "r"(w >> 16) : "memory"); }
                    nx += q[k] >= CELLN;
                }
                if (nx) ox = atoms_add(bars + MI_NOVF, nx);
                const int nz = node0 + tl + zero;
                if (stage && tl < NPC && ((ed.x != nz) | (ed.y != nz) | (ed.z != nz) | (ed.w != nz))) sts32(bars + MI_FLAGS, W_EBAD);
            }
            if (tl == 0) PROF(37);
            bar_sync(4, LT + 128);
            if (tl == 0) PROF(24);
            const uint32_t tag = ((epoch + zero) % 31u + 1u) << 27;
            {
                const uint32_t fl = lds32(bars + MI_FLAGS) | tag | (lds32(bars + MI_NOVF) > OVCAP / 2 ? W_OVF : 0u);
                uint4* const gp = p.cells + ((tl >> 2) * NCTA + cta) * 4 + (tl & 3);
#pragma unroll
                for (int r = 0; r < 2; ++r) {
                    uint4 w = lds128(sb + X_OUT + (tl + r * LT) * 16);
                    w.w |= fl;
                    if (r == 0 || tl + LT < RCTA * 4) gp[r * (LT / 4) * NCTA * 4] = w;
                }
            }
            warp_arrive(bars + B_SENT);
            if (tl == 0) { sts32(bars + MI_EPOCH, epoch); mbar_arrive(bars + B_EPO); }
            if (tl == 0) PROF(25);
#pragma unroll
            for (int k = 0; k < 5; ++k) {
                if (q[k] >= CELLN) sts32(bars + MI_OVF + min(ox, (uint32_t)OVCAP - 1) * 4, dd[k] << 14 | ss[k]);
                ox += q[k] >= CELLN;
            }
            uint4 r[4][2];
            auto load_rows = [&]() {
                if (stage) {
                    const char* xl = p.x + (lane & 15) * 16;
                    const char* r0 = row_ptr(xl, es.x); const char* r1 = row_ptr(xl, es.y); const char* r2 = row_ptr(xl, es.z); const char* r3 = row_ptr(xl, es.w);
                    r[0][0] = ldg_in(r0); r[0][1] = ldg_in(r0 + 256); r[1][0] = ldg_in(r1); r[1][1] = ldg_in(r1 + 256);
                    r[2][0] = ldg_in(r2); r[2][1] = ldg_in(r2 + 256); r[3][0] = ldg_in(r3); r[3][1] = ldg_in(r3 + 256);
                }
            };
            auto attend = [&]() {
                mbar_wait(bars + B_Q, 0);
                __syncwarp();
                if (!lds32(bars + MI_EBAD)) attention_chunks(r, sT, 64 + 2 * lw, lane);
                else { attention_generic(p, sT, 64 + 2 * lw, node0 + 64 + 2 * lw, lane); attention_generic(p, sT, 65 + 2 * lw, node0 + 65 + 2 * lw, lane); }
                fence_async_smem();
                warp_arrive(bars + B_Z);
                if (tl == 0) PROF(32);
            };
            if (rowcta) {
                mbar_wait(bars + B_SENT, 0);
                if (tl == LT - 1) sts32(sb + X_TAB + NPC * 64, 64);
                if (tl < 128) sts128(sb + X_ZERO + tl * 16, make_uint4(0, 0, 0, 0));
                uint4 c0, c1;
                const uint4* cp = p.cells + cta * (NCTA * 4) + tl;
                if (RGATE == 2) mbar_wait(bars + B_MI, 0);
                mbar_wait(bars + B_CGO, 0);
#pragma unroll 1
                for (int it = 0;; ++it) {
                    c0 = ld_relaxed4(cp); c1 = ld_relaxed4(cp + LT);
                    if (!__any_sync(0xffffffffu, ((c0.w ^ tag) | (c1.w ^ tag)) >> 27) || it >= SPIN_LIMIT) break;
                }
                if (tl == 0) PROF(26);
                if (RGATE == 1) mbar_wait(bars + B_MI, 0);
                if ((c0.w | c1.w) & W_OVF)  sts32(bars + MI_SLOW, 1);
                if ((c0.w | c1.w) & W_EBAD) sts32(bars + MI_EBAD, 1);
                uint32_t w[10] = {__byte_perm(c0.x, c0.z, 0x6610), __byte_perm(c0.x, c0.z, 0x7732), __byte_perm(c0.y, c0.w, 0x4410), __byte_perm(c0.y, c0.w, 0x5532), __byte_perm(c0.z, c0.w, 0x6610),
                                  __byte_perm(c1.x, c1.z, 0x6610), __byte_perm(c1.x, c1.z, 0x7732), __byte_perm(c1.y, c1.w, 0x4410), __byte_perm(c1.y, c1.w, 0x5532), __byte_perm(c1.z, c1.w, 0x6610)};
                {
                    uint32_t c[10];
#pragma unroll
                    for (int m = 0; m < 10; ++m) {
                        const uint32_t a = (w[m] >> 12) & 0xffcu;
                        c[m] = atoms_add(sb + X_CNT + a, a < NPC * 32);
                        w[m] = (w[m] & 0x3fffu) + (a << 15);
                    }
#pragma unroll
                    for (int m = 0; m < 10; ++m) w[m] += (c[m] > 7 ? 0x20000u : c[m]) << 14;
                }
                bar_sync(2, LT);
                if (tl == 0) { mbar_arrive(bars + B_LF); PROF(27); }
                if (lw < 3) {
                    const int d0 = min(tl, NPC - 8 + (tl & 7));
                    const int dl = d0 ^ ((d0 >> 3) & 1);
                    const uint4 n0 = lds128(sb + X_CNT + dl * 32), n1 = lds128(sb + X_CNT + dl * 32 + 16);
                    uint32_t pk = min(n0.x, 8u) + (min(n0.y, 8u) << 4) + (min(n0.z, 8u) << 8) + (min(n0.w, 8u) << 12) +
                                  (min(n1.x, 8u) << 16) + (min(n1.y, 8u) << 20) + (min(n1.z, 8u) << 24) + (min(n1.w, 8u) << 28);
                    pk = __funnelshift_r(pk, pk, 4 * lane);
                    uint32_t du = 0xf0000000u, ru = 0, b[8] = {0, 0, 0, 0, 0, 0, 0, 0};
                    auto code2 = [&](uint32_t b0, uint32_t b1) {
                        return __byte_perm(__float_as_uint(__uint_as_float(b0) * 8388608.f), __float_as_uint(__uint_as_float(b1) * 8388608.f), 0x7632);
                    };
                    uint32_t ta = (lane + 7) * 8;
                    auto pass_on = [&]() {
                        ru = __shfl_sync(0xffffffffu, ru, lane + 1, 8);
                        const uint32_t t0 = (code2(b[0], b[2]) >> 7) + code2(b[1], b[3]) * 2, t1 = (code2(b[4], b[6]) >> 7) + code2(b[5], b[7]) * 2;
                        asm volatile("st.shared.v2.u32 [%0], {%1, %2};" :: "r"(sb + X_TAB + ((dl * 64) | (ta & 56))), "r"(t0), "r"(t1) : "memory");
                        ta += 8;
                    };
                    auto take = [&](uint32_t& m, uint32_t& bit, uint32_t n, int c) {
                        asm("{\n.reg .pred p;\n.reg .b32 u;\nsetp.gt.u32 p, %2, %3;\nadd.u32 u, %0, -1;\nlop3.b32 %1, %0, u, 0, 0x30;\n@p and.b32 %0, %0, u;\n}"
                            : "+r"(m), "=r"(bit) : "r"(n), "r"(c));
                    };
#pragma unroll 1
                    for (int k = 0; k < 8; ++k) {
                        const uint32_t n = pk & 15u;
                        const bool big = __any_sync(0xffffffffu, n > 6);
                        pk >>= 4;
                        pass_on();
                        const uint32_t fr = ~(du | ru);
                        uint32_t m = fr;
#pragma unroll
                        for (int c = 0; c < 6; ++c) take(m, b[c], n, c);
                        if (big) { take(m, b[6], n, 6); take(m, b[7], n, 7); }
                        du |= m ^ fr;
                        ru |= m ^ fr;
                    }
                    pass_on();
                    sts32(sb + X_RU + d0 * 4, ru);
                }
                if (tl == 0) PROF(49);
                if (LGATE >= 0) { mbar_wait(bars + B_MI, 0); mbar_wait(bars + B_K + LGATE * 8, 1); }
                load_rows();
                bar_sync(2, LT);
                if (tl == 0) PROF(28);
                const int v = LT - 1 - tl;
                if (lw >= 6 && v < 40) {
                    const uint4 b = lds128(sb + X_RU + (v >> 2) * 32), e = lds128(sb + X_RU + (v >> 2) * 32 + 16);
                    const uint32_t f2 = b.x & b.y & b.z & b.w;
                    const uint32_t s0 = (f2 & e.x) | (~f2 & b.x), s1 = (f2 & e.y) | (~f2 & b.y), s2 = (f2 & e.z) | (~f2 & b.z);
                    const uint32_t f1 = s0 & s1, f0 = (f1 & s2) | (~f1 & s0);
                    uint32_t u[4];
#pragma unroll
                    for (int k = 0; k < 4; ++k) {
                        const int sh = (v & 3) * 8 + 2 * k;
                        u[k] = ((((f0 >> sh) & 3u) * 0x8001u) & 0x10001u) + ((((f1 >> sh) & 3u) * 0x10002u) & 0x20002u) + ((((f2 >> sh) & 3u) * 0x20004u) & 0x40004u);
                    }
                    sts128(sb + X_DEF + v * 16, make_uint4(u[0], u[1], u[2], u[3]));
                }
                {
                    uint32_t rd[10];
#pragma unroll
                    for (int m = 0; m < 10; ++m) asm volatile("ld.shared.u8 %0, [%1];" : "=r"(rd[m]) : "r"(sb + X_TAB + min(w[m] >> 14, NPC * 64u)) : "memory");
#pragma unroll
                    for (int m = 0; m < 10; ++m) {
                        rd[m] -= 1;
                        if (rd[m] < 48) sts16(sb + X_IMG + ((w[m] >> 14) & ~63u) + min(rd[m], 31u) * 2, w[m] & 0x3fffu);
                        w[m] |= rd[m] & 0x80000000u;
                    }
                    if (__any_sync(0xffffffffu, (int)(w[0] | w[1] | w[2] | w[3] | w[4] | w[5] | w[6] | w[7] | w[8] | w[9]) < 0)) {
                        uint32_t n = 0;
#pragma unroll
                        for (int m = 0; m < 10; ++m) n += w[m] >> 31;
                        uint32_t o = atoms_add(bars + MI_NOVF, n);
#pragma unroll
                        for (int m = 0; m < 10; ++m) {
                            if ((int)w[m] < 0) sts32(bars + MI_OVF + min(o, (uint32_t)OVCAP - 1) * 4, ((w[m] >> 6) & 0x1fc000u) + (w[m] & 0x3fffu) + (node0 * 16384 - 8));
                            o += w[m] >> 31;
                        }
                    }
                }
                bar_sync(2, LT);
                if (tl == 0) PROF(29);
#pragma unroll 1
                for (int set = lw; set < 10; set += lw >= 3 && lw < 5 ? 5 : 10) publish(set);
            }
            warp_arrive(bars + B_XF);
            if (tl == 0) PROF(30);
            if (rowcta) attend();
            mbar_wait(bars + B_GO, 0);
            fetch0();
        }
        const uint32_t stg = sb + SM_X + (lane & 15) * 16;
        const uint32_t lt = list_tag(lds32(bars + MI_EPOCH)), base = sS - (lt & 0xffffu) * 16;
        const int nu = UPQ + (quarter == 3);
        int u = wi;
        auto unit = [&](Unit& c, Unit& n) {
#pragma unroll 1
            for (int it = 0;; ++it) {
                if (!__any_sync(0xffffffffu, unit_stale(c, lt) > (it < SPIN_LIMIT ? 0u : 0xffffu))) break;
                fetch(c, u);
            }
            if (u >= 4 * AW) { mbar_wait(bars + B_TF, 0); __syncwarp(); }
            if (u + AW < nu) fetch(n, u + AW);
            agg_unit(c, base, stg + u * 256, lt);
            warp_arrive(bars + B_RND + min((u * 171) >> 11, 12) * 8);
            u += AW;
        };
        mbar_wait(bars + B_S, 0);
        if (rowcta) mbar_wait(bars + B_VE, 0);
        __syncwarp();
        if (tid == 0) PROF(20);
        if (tid == GT) PROF(4);
#pragma unroll 1
        for (;;) {
            unit(x0, x1);
            if (u >= nu) break;
            unit(x1, x0);
            if (u >= nu) break;
        }
        if (WPROF) { if (lane == 0) PROF(24 + wi); } else if (tid == 0) PROF(21);
        if (rowcta && slow_cta()) { mbar_wait(bars + B_RV, 0); local_generic(p, node0, wi, lane); }
    }
    PROF_FLUSH();
}

typedef CUresult (*EncodeFn)(CUtensorMap*, CUtensorMapDataType, cuuint32_t, void*, const cuuint64_t*, const cuuint64_t*,
                             const cuuint32_t*, const cuuint32_t*, CUtensorMapInterleave, CUtensorMapSwizzle,
                             CUtensorMapL2promotion, CUtensorMapFloatOOBfill);

static void make_map(EncodeFn enc, CUtensorMap* m, const void* ptr, int rows, int box_cols, int box_rows) {
    cuuint64_t dims[2] = {(cuuint64_t)D, (cuuint64_t)rows};
    cuuint64_t strides[1] = {(cuuint64_t)D * 2};
    cuuint32_t box[2] = {(cuuint32_t)box_cols, (cuuint32_t)box_rows};
    cuuint32_t es[2] = {1u, 1u};
    enc(m, CU_TENSOR_MAP_DATA_TYPE_BFLOAT16, 2, const_cast<void*>(ptr), dims, strides, box, es, CU_TENSOR_MAP_INTERLEAVE_NONE,
        box_cols == 64 ? CU_TENSOR_MAP_SWIZZLE_128B : CU_TENSOR_MAP_SWIZZLE_NONE,
        box_cols == 64 ? PROMO : CU_TENSOR_MAP_L2_PROMOTION_NONE, CU_TENSOR_MAP_FLOAT_OOB_FILL_NONE);
}
static void make_map3(EncodeFn enc, CUtensorMap* m, const void* ptr, int rows, int box_rows) {
    cuuint64_t dims[3] = {64, (cuuint64_t)rows, 4};
    cuuint64_t strides[2] = {(cuuint64_t)D * 2, 128};
    cuuint32_t box[3] = {64u, (cuuint32_t)box_rows, 4u};
    cuuint32_t es[3] = {1u, 1u, 1u};
    enc(m, CU_TENSOR_MAP_DATA_TYPE_BFLOAT16, 3, const_cast<void*>(ptr), dims, strides, box, es, CU_TENSOR_MAP_INTERLEAVE_NONE,
        CU_TENSOR_MAP_SWIZZLE_128B, CU_TENSOR_MAP_L2_PROMOTION_L2_256B, CU_TENSOR_MAP_FLOAT_OOB_FILL_NONE);
}

}

extern "C" void kernel_launch(void* const* d_in, const int* in_sizes, int n_in, void* d_out, int out_size) {
    using namespace gk;
    (void)n_in; (void)out_size;
    static EncodeFn enc = nullptr;
    static void *m_ptr, *cells_ptr, *sync_ptr, *h_ptr, *idx_ptr;
    if (!enc) {
        void* fn = nullptr;
        cudaDriverEntryPointQueryResult qr;
        cudaGetDriverEntryPoint("cuTensorMapEncodeTiled", &fn, cudaEnableDefault, &qr);
        enc = (EncodeFn)fn;
        cudaGetSymbolAddress(&m_ptr, g_M);
        cudaGetSymbolAddress(&cells_ptr, g_cells);
        cudaGetSymbolAddress(&sync_ptr, g_sync);
        cudaGetSymbolAddress(&h_ptr, g_H);
        cudaGetSymbolAddress(&idx_ptr, g_idx);
        cudaFuncSetAttribute(fused_kernel, cudaFuncAttributeMaxDynamicSharedMemorySize, SM_ALLOC);
    }
    if (in_sizes[5] != N || in_sizes[0] != N * D) return;
    Params p;
    p.src  = (const int*)d_in[1];
    p.dst  = (const int*)d_in[2];
    p.esrc = (const int*)d_in[3];
    p.edst = (const int*)d_in[4];
    p.sync = (uint32_t*)sync_ptr;
    p.x    = (const char*)d_in[0];
    p.dis  = (const __nv_bfloat16*)d_in[5];
    p.wv   = (const char*)d_in[9];
    p.cells = (uint4*)cells_ptr;
    p.H    = (uint4*)h_ptr;
    p.idx  = (uint4*)idx_ptr;
    p.M    = (uint2*)m_ptr;
    p.out  = (uint4*)d_out;
    p.E  = in_sizes[1];
    p.Ee = in_sizes[3];
    p.chunk = (((p.E + NCTA - 1) / NCTA) + 1) & ~1;
    p.force_slow  = (p.chunk > 5 * LT || (p.E & 1)) ? 1 : 0;
    p.force_eslow = (p.Ee != 4 * N) ? 1 : 0;
    p.Efast = p.force_slow ? 0 : p.E;

    CUtensorMap tmX, tmWl, tmM, tmWv, tmR, tmO, tmG, tmQ, tmK, tmV3;
    make_map(enc, &tmX, d_in[0], N, 64, NPC);
    make_map3(enc, &tmWl, d_in[6], D, 64);
    make_map3(enc, &tmM, m_ptr, D, 64);
    make_map3(enc, &tmWv, d_in[9], D, 64);
    make_map(enc, &tmR, d_out, N, 64, 16);
    make_map(enc, &tmO, d_out, N, 8, 192);
    make_map(enc, &tmG, d_in[0], N, 256, 1);
    make_map3(enc, &tmQ, d_in[7], D, 16);
    make_map3(enc, &tmK, d_in[8], D, 32);
    make_map3(enc, &tmV3, d_in[9], D, 16);
    fused_kernel<<<NCTA, NTHR, SM_ALLOC, cudaStreamPerThread>>>(p, tmX, tmWl, tmM, tmWv, tmR, tmO, tmG, tmQ, tmK, tmV3);
}
```

```cpp
#include <cuda_runtime.h>
#include <cuda_bf16.h>
#include <cuda.h>
#include <stdint.h>

#define PROFILE 0

namespace gk {

constexpr int N      = 10000;
constexpr int D      = 256;
constexpr int NPC    = 80;
constexpr int NCTA   = 128;
constexpr int RCTA   = N / NPC;
constexpr int NSET   = N / 8;
constexpr int GW     = 16;
constexpr int LW     = 8;
constexpr int AW     = GW + LW;
constexpr int GT     = GW * 32, LT = LW * 32;
constexpr int NTHR   = (AW + 4) * 32;
constexpr int UPQ    = 156;
constexpr int OVCAP  = 128;
#define SPINB 18
constexpr int SPIN_LIMIT = 1 << SPINB;

constexpr int KB      = NPC * 128;
constexpr int UNIT    = 8192;
constexpr int SM_S    = 0;
constexpr int SM_X    = 20 * UNIT;
constexpr int SM_T    = 23 * UNIT;
constexpr int SM_MISC = SM_T + 4 * KB;
constexpr int SM_END  = SM_MISC + 2464;
constexpr int SLICE_END = 128 + N * 16;
constexpr int X_OUT  = SM_X + UNIT;
constexpr int X_TAB  = X_OUT;
constexpr int X_RU   = X_TAB + NPC * 64 + 16;
constexpr int X_DEF  = X_RU + NPC * 4;
constexpr int X_ZERO = X_OUT + UNIT - 2048;
constexpr int X_IMG  = X_OUT + UNIT;
constexpr int X_CNT  = X_IMG + NPC * 64;
static_assert(X_DEF + 640 <= X_ZERO && X_CNT + NPC * 32 + 128 <= SM_T, "list scratch");
constexpr int B_K = 0, B_QK = 32, B_EPO = 40,
              B_A = 48,
              B_F = 176, B_HS = 272, B_Q = 280, B_R = 288,
              B_GO = 296, B_LF = 304, B_TF = 312, B_RGO = 320, B_CGO = 328, B_MI = 336, B_HR = 344,
              B_Z = 352,
              B_FA = 360, B_XF = 392, B_SENT = 400, B_S = 408, B_VE = 416,
              B_RND = 424;
constexpr int B_HV = 528, B_RV = 536;
constexpr int MI_EPOCH = 544, MI_EBAD = 548, MI_SLOW = 552, MI_NOVF = 556, MI_FLAGS = 560;
constexpr int MI_OVF  = 1280;
constexpr int MI_ES   = 768;
constexpr int MI_PCNT = 1792;
constexpr int MI_DIS  = 2304;
constexpr int A0 = 0, A1 = 4, A2 = 8, A3 = 12, A4 = 16, A5 = 19;
constexpr uint32_t A_TILES = A3 | A1 << 8 | A2 << 16 | A0 << 24;
#define PROMO CU_TENSOR_MAP_L2_PROMOTION_L2_128B
#define EFETCH 1
#define VPF 1
#define RPER 0
#define ER 2
#define G3 1
#define XORD 0x04156273
#define LGATE 1
#define AUNRV 1
constexpr int AUNR = AUNRV;
#define WPROF 0
#define RGATE 0
#define QLF 0
#define MW 2
#define SROT 1
#define HGATE 0
#define CHK1 0
#define HPER 160
#define HRW 1
#define T0BAR B_CGO

constexpr uint32_t W_OVF = 1u << 24, W_EBAD = 1u << 25;
constexpr int CELLN = 20;

__device__ uint4         g_cells[RCTA * NCTA * 4];
__device__ uint4         g_H[32 * N];
__device__ uint4         g_idx[NSET * 32];
__device__ __nv_bfloat16 g_M[D * D];
__device__ uint32_t      g_sync[24 * 32];
constexpr int SY_M = 16 * 32, SY_H = 17 * 32, SY_L = 18 * 32, SY_R = 19 * 32, SY_SLOW = 20 * 32;
#define PROF(i) do {} while (0)
#define PROF_FLUSH() do {} while (0)
constexpr int SM_ALLOC = SM_END;
static_assert(SM_ALLOC <= 232448, "shared memory");

struct Params {
    const int* src; const int* dst;
    uint32_t* sync;
    const int* esrc; const int* edst;
    int Efast, chunk;
    const __nv_bfloat16* dis;
    const char* x; const char* wv;
    uint4* cells; uint2* M;
    int force_slow, force_eslow;
    uint4* idx; uint4* H; uint4* out;
    int E, Ee;
};

__device__ __forceinline__ uint32_t s32(const void* p) { return (uint32_t)__cvta_generic_to_shared(p); }
__device__ __forceinline__ void mbar_init(uint32_t a, uint32_t cnt) { asm volatile("mbarrier.init.shared.b64 [%0], %1;" :: "r"(a), "r"(cnt) : "memory"); }
__device__ __forceinline__ void mbar_arrive(uint32_t a) { asm volatile("mbarrier.arrive.shared.b64 _, [%0];" :: "r"(a) : "memory"); }
__device__ __forceinline__ void mbar_expect(uint32_t a, uint32_t bytes) { asm volatile("mbarrier.arrive.expect_tx.shared.b64 _, [%0], %1;" :: "r"(a), "r"(bytes) : "memory"); }
__device__ __forceinline__ void mbar_wait(uint32_t a, uint32_t parity) {
    uint32_t ok = 0;
#pragma unroll 1
    for (int it = 0; it < SPIN_LIMIT && !ok; ++it)
        asm volatile("{\n.reg .pred p;\nmbarrier.try_wait.parity.shared.b64 p, [%1], %2;\nselp.u32 %0, 1, 0, p;\n}"
                     : "=r"(ok) : "r"(a), "r"(parity) : "memory");
}
__device__ __forceinline__ bool elect() { uint32_t r; asm volatile("{\n.reg .pred p;\nelect.sync _|p, 0xffffffff;\nselp.u32 %0, 1, 0, p;\n}" : "=r"(r) :: "memory"); return r; }
__device__ __forceinline__ void warp_arrive(uint32_t a) {
    asm volatile("{\n.reg .pred p;\nelect.sync _|p, 0xffffffff;\n@p mbarrier.arrive.shared.b64 _, [%0];\n}" :: "r"(a) : "memory");
}
__device__ __forceinline__ void bar_sync(int id, int n)   { __syncwarp(); asm volatile("bar.sync %0, %1;"   :: "r"(id), "r"(n) : "memory"); }
__device__ __forceinline__ void bar_arrive(int id, int n) { __syncwarp(); asm volatile("bar.arrive %0, %1;" :: "r"(id), "r"(n) : "memory"); }
__device__ __forceinline__ void fence_async_smem() { asm volatile("fence.proxy.async.shared::cta;" ::: "memory"); }
__device__ __forceinline__ void fence_async_gmem() { asm volatile("fence.proxy.async.global;" ::: "memory"); }
__device__ __forceinline__ void tma2d(uint32_t dst, const CUtensorMap* tm, int c0, int c1, uint32_t bar) {
    asm volatile("cp.async.bulk.tensor.2d.shared::cluster.global.mbarrier::complete_tx::bytes [%0], [%1, {%3, %4}], [%2];"
                 :: "r"(dst), "l"(tm), "r"(bar), "r"(c0), "r"(c1) : "memory");
}
__device__ __forceinline__ void tma3d(uint32_t dst, const CUtensorMap* tm, int row, uint32_t bar) {
    asm volatile("cp.async.bulk.tensor.3d.shared::cluster.global.mbarrier::complete_tx::bytes [%0], [%1, {%4, %3, %4}], [%2];"
                 :: "r"(dst), "l"(tm), "r"(bar), "r"(row), "r"(0) : "memory");
}
__device__ __forceinline__ void tma2d_store(const CUtensorMap* tm, uint32_t src, int c0, int c1) {
    asm volatile("cp.async.bulk.tensor.2d.global.shared::cta.bulk_group [%0, {%2, %3}], [%1];"
                 :: "l"(tm), "r"(src), "r"(c0), "r"(c1) : "memory");
}
__device__ __forceinline__ void tma2d_add(const CUtensorMap* tm, uint32_t src, int c0, int c1) {
    asm volatile("cp.reduce.async.bulk.tensor.2d.global.shared::cta.add.bulk_group [%0, {%2, %3}], [%1];"
                 :: "l"(tm), "r"(src), "r"(c0), "r"(c1) : "memory");
}
__device__ __forceinline__ void bulk_load(uint32_t dst, const void* src, uint32_t bytes, uint32_t bar) {
    asm volatile("cp.async.bulk.shared::cluster.global.mbarrier::complete_tx::bytes [%0], [%1], %2, [%3];"
                 :: "r"(dst), "l"(src), "r"(bytes), "r"(bar) : "memory");
}
__device__ __forceinline__ void bulk_store(void* dst, uint32_t src, uint32_t bytes) {
    asm volatile("cp.async.bulk.global.shared::cta.bulk_group [%0], [%1], %2;" :: "l"(dst), "r"(src), "r"(bytes) : "memory");
}
__device__ __forceinline__ uint32_t clk() { uint32_t c; asm volatile("mov.u32 %0, %%clock;" : "=r"(c) :: "memory"); return c; }
__device__ __forceinline__ void wait_clk(uint32_t t) { while ((int)(clk() - t) < 0) {} }
__device__ __forceinline__ void bulk_commit() { asm volatile("cp.async.bulk.commit_group;" ::: "memory"); }
template <int K> __device__ __forceinline__ void bulk_wait_read() { asm volatile("cp.async.bulk.wait_group.read %0;" :: "n"(K) : "memory"); }
__device__ __forceinline__ void prefetch_map(const CUtensorMap* tm) { asm volatile("prefetch.tensormap [%0];" :: "l"(tm) : "memory"); }
__device__ __forceinline__ uint4 lds128(uint32_t a) { uint4 v; asm volatile("ld.shared.v4.u32 {%0,%1,%2,%3}, [%4];" : "=r"(v.x), "=r"(v.y), "=r"(v.z), "=r"(v.w) : "r"(a) : "memory"); return v; }
__device__ __forceinline__ void sts128(uint32_t a, uint4 v) { asm volatile("st.shared.v4.u32 [%0], {%1,%2,%3,%4};" :: "r"(a), "r"(v.x), "r"(v.y), "r"(v.z), "r"(v.w) : "memory"); }
__device__ __forceinline__ uint32_t lds32(uint32_t a) { uint32_t v; asm volatile("ld.shared.u32 %0, [%1];" : "=r"(v) : "r"(a) : "memory"); return v; }
__device__ __forceinline__ void sts32(uint32_t a, uint32_t v) { asm volatile("st.shared.u32 [%0], %1;" :: "r"(a), "r"(v) : "memory"); }
__device__ __forceinline__ void sts16(uint32_t a, uint32_t v) { asm volatile("st.shared.u16 [%0], %1;" :: "r"(a), "h"((unsigned short)v) : "memory"); }
__device__ __forceinline__ uint32_t atoms_add(uint32_t a, uint32_t x) { uint32_t v; asm volatile("atom.shared.add.u32 %0, [%1], %2;" : "=r"(v) : "r"(a), "r"(x) : "memory"); return v; }
__device__ __forceinline__ uint32_t ld_relaxed(const uint32_t* p) { uint32_t v; asm volatile("ld.relaxed.gpu.global.u32 %0, [%1];" : "=r"(v) : "l"(p) : "memory"); return v; }
__device__ __forceinline__ uint4 ld_relaxed4(const uint4* p) { uint4 v; asm volatile("ld.relaxed.gpu.global.L1::no_allocate.v4.u32 {%0,%1,%2,%3}, [%4];" : "=r"(v.x), "=r"(v.y), "=r"(v.z), "=r"(v.w) : "l"(p) : "memory"); return v; }
__device__ __forceinline__ uint32_t ld_acquire(const uint32_t* p) { uint32_t v; asm volatile("ld.acquire.gpu.global.u32 %0, [%1];" : "=r"(v) : "l"(p) : "memory"); return v; }
__device__ __forceinline__ void st_relaxed(uint32_t* p, uint32_t v) { asm volatile("st.relaxed.gpu.global.u32 [%0], %1;" :: "l"(p), "r"(v) : "memory"); }
__device__ __forceinline__ void red_relaxed(uint32_t* p) { asm volatile("red.relaxed.gpu.global.add.u32 [%0], 1;" :: "l"(p) : "memory"); }
__device__ __forceinline__ uint32_t list_tag(uint32_t epoch) { return (epoch % 3u + 1u) * 0x40004000u; }
__device__ __forceinline__ void red_release(uint32_t* p) { asm volatile("red.release.gpu.global.add.u32 [%0], 1;" :: "l"(p) : "memory"); }
__device__ __forceinline__ void wait_count(const uint32_t* p, uint32_t target) {
#pragma unroll 1
    for (int it = 0; it < SPIN_LIMIT; ++it)
        if ((int)(ld_acquire(p) - target) >= 0) break;
}
__device__ __forceinline__ bool mbar_test(uint32_t a, uint32_t parity) {
    uint32_t ok;
    asm volatile("{\n.reg .pred p;\nmbarrier.test_wait.parity.shared.b64 p, [%1], %2;\nselp.u32 %0, 1, 0, p;\n}" : "=r"(ok) : "r"(a), "r"(parity) : "memory");
    return __all_sync(0xffffffffu, ok);
}
__device__ __forceinline__ uint4 ldg_in(const void* p) { uint4 v; asm volatile("ld.global.nc.L1::no_allocate.v4.u32 {%0,%1,%2,%3}, [%4];" : "=r"(v.x), "=r"(v.y), "=r"(v.z), "=r"(v.w) : "l"(p)); return v; }
__device__ __forceinline__ uint4 ldg_sc(const void* p) { uint4 v; asm volatile("ld.global.L1::no_allocate.v4.u32 {%0,%1,%2,%3}, [%4];" : "=r"(v.x), "=r"(v.y), "=r"(v.z), "=r"(v.w) : "l"(p) : "memory"); return v; }
__device__ __forceinline__ void red_row(uint4* p, uint4 v) { asm volatile("red.relaxed.gpu.global.add.noftz.v4.bf16x2 [%0], {%1,%2,%3,%4};" :: "l"(p), "r"(v.x), "r"(v.y), "r"(v.z), "r"(v.w) : "memory"); }
__device__ __forceinline__ uint32_t pack_bf16(float lo, float hi) { uint32_t r; asm("cvt.rn.bf16x2.f32 %0, %1, %2;" : "=r"(r) : "f"(hi), "f"(lo)); return r; }
__device__ __forceinline__ float blo(uint32_t v) { return __uint_as_float(v << 16); }
__device__ __forceinline__ float bhi(uint32_t v) { return __uint_as_float(v & 0xffff0000u); }
__device__ __forceinline__ const char* row_ptr(const char* base, uint32_t row) {
    uint64_t r; asm("mad.wide.u32 %0, %1, 512, %2;" : "=l"(r) : "r"(row), "l"((uint64_t)base)); return (const char*)r;
}

constexpr uint32_t DESC_HI = 64u | (1u << 30);
__device__ __forceinline__ uint32_t desc_lo(uint32_t addr) { return ((addr & 0x3FFFF) >> 4) | (1u << 16); }
__device__ __forceinline__ void wg_fence()  { asm volatile("wgmma.fence.sync.aligned;" ::: "memory"); }
__device__ __forceinline__ void wg_commit() { asm volatile("wgmma.commit_group.sync.aligned;" ::: "memory"); }
template <int K> __device__ __forceinline__ void wg_wait() { asm volatile("wgmma.wait_group.sync.aligned %0;" :: "n"(K) : "memory"); }
#define GK_ACC(c) c(d[0]), c(d[1]), c(d[2]), c(d[3]), c(d[4]), c(d[5]), c(d[6]), c(d[7]), c(d[8]), c(d[9]), \
    c(d[10]), c(d[11]), c(d[12]), c(d[13]), c(d[14]), c(d[15]), c(d[16]), c(d[17]), c(d[18]), c(d[19]), \
    c(d[20]), c(d[21]), c(d[22]), c(d[23]), c(d[24]), c(d[25]), c(d[26]), c(d[27]), c(d[28]), c(d[29]), \
    c(d[30]), c(d[31]), c(d[32]), c(d[33]), c(d[34]), c(d[35]), c(d[36]), c(d[37]), c(d[38]), c(d[39])
#define GK_WGMMA(P) "{\n.reg .pred p;\n.reg .b64 da, db;\nsetp.ne.b32 p, " P ", 0;\nmov.b64 da, {%40, %42};\nmov.b64 db, {%41, %42};\n" \
    "wgmma.mma_async.sync.aligned.m64n80k16.f32.bf16.bf16 " \
    "{%0,%1,%2,%3,%4,%5,%6,%7,%8,%9,%10,%11,%12,%13,%14,%15,%16,%17,%18,%19," \
    "%20,%21,%22,%23,%24,%25,%26,%27,%28,%29,%30,%31,%32,%33,%34,%35,%36,%37,%38,%39}, da, db, p, 1, 1, 1, 0;\n}\n"
template <bool FIRST>
__device__ __forceinline__ void wgmma80(float (&d)[40], uint32_t alo, uint32_t blo_) {
    if (FIRST) asm volatile(GK_WGMMA("0") : GK_ACC("=f") : "r"(alo), "r"(blo_), "r"(DESC_HI));
    else       asm volatile(GK_WGMMA("1") : GK_ACC("+f") : "r"(alo), "r"(blo_), "r"(DESC_HI));
}
template <int KQ>
__device__ __forceinline__ void gemm_quarter(float (&d)[40], uint32_t unit, uint32_t tile, uint32_t bar, uint32_t parity, uint32_t rel = 0) {
    mbar_wait(bar + KQ * 8, parity);
    __syncwarp();
    const uint32_t a = desc_lo(unit), b = desc_lo(tile) + ((KQ * KB) >> 4);
    wg_fence();
    wgmma80<KQ == 0>(d, a, b);
    if (KQ) { wg_commit(); wg_wait<1>(); warp_arrive(rel); }
    wgmma80<false>(d, a + 128, b + 2);
    wgmma80<false>(d, a + 256, b + 4);
    wgmma80<false>(d, a + 384, b + 6);
    wg_commit();
}
__device__ __forceinline__ void stsm4t(uint32_t a, uint32_t r0, uint32_t r1, uint32_t r2, uint32_t r3) {
    asm volatile("stmatrix.sync.aligned.m8n8.x4.trans.shared.b16 [%0], {%1,%2,%3,%4};" :: "r"(a), "r"(r0), "r"(r1), "r"(r2), "r"(r3) : "memory");
}
__device__ __forceinline__ void stsm4(uint32_t a, uint32_t r0, uint32_t r1, uint32_t r2, uint32_t r3) {
    asm volatile("stmatrix.sync.aligned.m8n8.x4.shared.b16 [%0], {%1,%2,%3,%4};" :: "r"(a), "r"(r0), "r"(r1), "r"(r2), "r"(r3) : "memory");
}
__device__ __forceinline__ uint4 ldsm4(uint32_t a) {
    uint4 v; asm volatile("ldmatrix.sync.aligned.m8n8.x4.shared.b16 {%0,%1,%2,%3}, [%4];" : "=r"(v.x), "=r"(v.y), "=r"(v.z), "=r"(v.w) : "r"(a) : "memory"); return v;
}
__device__ __forceinline__ void mma16816(float (&c)[4], uint32_t a0, uint32_t a1, uint32_t a2, uint32_t a3, uint32_t b0, uint32_t b1) {
    asm volatile("mma.sync.aligned.m16n8k16.row.col.f32.bf16.bf16.f32 {%0,%1,%2,%3}, {%4,%5,%6,%7}, {%8,%9}, {%0,%1,%2,%3};"
        : "+f"(c[0]), "+f"(c[1]), "+f"(c[2]), "+f"(c[3]) : "r"(a0), "r"(a1), "r"(a2), "r"(a3), "r"(b0), "r"(b1));
}
__device__ __forceinline__ void pack_acc(uint32_t (&h)[20], const float (&d)[40]) {
#pragma unroll
    for (int i = 0; i < 20; ++i) h[i] = pack_bf16(d[2 * i], d[2 * i + 1]);
}
__device__ __forceinline__ void store_tile(const uint32_t (&h)[20], uint32_t tile, int mt, int w4, int lane) {
    const int r = lane & 7;
    const uint32_t base = tile + mt * KB + (((lane >> 4) * 8 + r) * 128) + (((2 * w4 + ((lane >> 3) & 1)) ^ r) << 4);
#pragma unroll
    for (int i = 0; i < 5; ++i) stsm4t(base + i * 2048, h[4 * i], h[4 * i + 1], h[4 * i + 2], h[4 * i + 3]);
}
__device__ __forceinline__ void fma8(float (&a)[8], float w, const uint4& v) {
    a[0] = fmaf(w, blo(v.x), a[0]); a[1] = fmaf(w, bhi(v.x), a[1]);
    a[2] = fmaf(w, blo(v.y), a[2]); a[3] = fmaf(w, bhi(v.y), a[3]);
    a[4] = fmaf(w, blo(v.z), a[4]); a[5] = fmaf(w, bhi(v.z), a[5]);
    a[6] = fmaf(w, blo(v.w), a[6]); a[7] = fmaf(w, bhi(v.w), a[7]);
}
__device__ __forceinline__ float dot8(const float (&q)[8], const uint4& v) {
    float s = q[0] * blo(v.x);
    s = fmaf(q[1], bhi(v.x), s); s = fmaf(q[2], blo(v.y), s); s = fmaf(q[3], bhi(v.y), s);
    s = fmaf(q[4], blo(v.z), s); s = fmaf(q[5], bhi(v.z), s); s = fmaf(q[6], blo(v.w), s); s = fmaf(q[7], bhi(v.w), s);
    return s;
}
__device__ __forceinline__ uint4 pack8(const float (&a)[8], float s) {
    return make_uint4(pack_bf16(a[0] * s, a[1] * s), pack_bf16(a[2] * s, a[3] * s), pack_bf16(a[4] * s, a[5] * s), pack_bf16(a[6] * s, a[7] * s));
}
__device__ __forceinline__ uint32_t hmul2(uint32_t a, uint32_t b) { uint32_t d; asm("mul.rn.bf16x2 %0, %1, %2;" : "=r"(d) : "r"(a), "r"(b)); return d; }
__device__ __forceinline__ uint32_t tile_chunk(uint32_t tile, int r, int c) {
    return tile + (c >> 3) * KB + r * 128 + (((c & 7) ^ (r & 7)) << 4);
}
__device__ __forceinline__ uint32_t wsum4(const uint32_t (&a)[4], uint32_t r0, uint32_t r1, uint32_t r2, uint32_t r3) {
    uint32_t z;
    asm("{\n.reg .b32 t;\nmul.rn.bf16x2 t, %1, %5;\nfma.rn.bf16x2 t, %2, %6, t;\nfma.rn.bf16x2 t, %3, %7, t;\nfma.rn.bf16x2 %0, %4, %8, t;\n}"
        : "=r"(z) : "r"(a[0]), "r"(a[1]), "r"(a[2]), "r"(a[3]), "r"(r0), "r"(r1), "r"(r2), "r"(r3));
    return z;
}
__device__ __forceinline__ void softmax4(const float (&s)[4], const float (&u)[4], int lane, uint32_t (&a)[4]) {
    const bool b = lane & 4, c = lane & 8;
    const float k0 = (b ? u[1] : s[0]) + __shfl_xor_sync(0xffffffffu, b ? s[1] : u[0], 4);
    const float k1 = (b ? u[3] : s[2]) + __shfl_xor_sync(0xffffffffu, b ? s[3] : u[2], 4);
    const float e = (c ? k1 : k0) + __shfl_xor_sync(0xffffffffu, c ? k0 : k1, 9);
    float pe;
    asm("ex2.approx.ftz.f32 %0, %1;" : "=f"(pe) : "f"(e * (0.0625f * 1.4426950408889634f)));
    const int l0 = (lane >> 4) * 18;
    const float p0 = __shfl_sync(0xffffffffu, pe, l0), p1 = __shfl_sync(0xffffffffu, pe, l0 + 9);
    const float p2 = __shfl_sync(0xffffffffu, pe, l0 + 4), p3 = __shfl_sync(0xffffffffu, pe, l0 + 13);
    float inv;
    asm("rcp.approx.ftz.f32 %0, %1;" : "=f"(inv) : "f"(((p0 + p1) + (p2 + p3)) + 1e-9f));
    a[0] = pack_bf16(p0 * inv, p0 * inv); a[1] = pack_bf16(p1 * inv, p1 * inv);
    a[2] = pack_bf16(p2 * inv, p2 * inv); a[3] = pack_bf16(p3 * inv, p3 * inv);
}
__device__ __forceinline__ void attention_chunks(const uint4 (&r)[4][2], uint32_t tile, int node, int lane) {
    const uint32_t qa = tile_chunk(tile, node + (lane >> 4), lane & 15);
    const uint4 q0 = lds128(qa), q1 = lds128(qa + 2 * KB);
    float s[4] = {0.f, 0.f, 0.f, 0.f}, u[4] = {0.f, 0.f, 0.f, 0.f};
    mma16816(s, r[0][0].x, r[1][0].x, r[0][0].y, r[1][0].y, q0.x, q0.y); mma16816(u, r[2][0].x, r[3][0].x, r[2][0].y, r[3][0].y, q0.x, q0.y);
    mma16816(s, r[0][0].z, r[1][0].z, r[0][0].w, r[1][0].w, q0.z, q0.w); mma16816(u, r[2][0].z, r[3][0].z, r[2][0].w, r[3][0].w, q0.z, q0.w);
    mma16816(s, r[0][1].x, r[1][1].x, r[0][1].y, r[1][1].y, q1.x, q1.y); mma16816(u, r[2][1].x, r[3][1].x, r[2][1].y, r[3][1].y, q1.x, q1.y);
    mma16816(s, r[0][1].z, r[1][1].z, r[0][1].w, r[1][1].w, q1.z, q1.w); mma16816(u, r[2][1].z, r[3][1].z, r[2][1].w, r[3][1].w, q1.z, q1.w);
    uint32_t a[4];
    softmax4(s, u, lane, a);
#pragma unroll
    for (int h = 0; h < 2; ++h)
        sts128(qa + h * 2 * KB, make_uint4(wsum4(a, r[0][h].x, r[1][h].x, r[2][h].x, r[3][h].x), wsum4(a, r[0][h].y, r[1][h].y, r[2][h].y, r[3][h].y),
                                           wsum4(a, r[0][h].z, r[1][h].z, r[2][h].z, r[3][h].z), wsum4(a, r[0][h].w, r[1][h].w, r[2][h].w, r[3][h].w)));
}
__device__ __forceinline__ void attention_frags(const uint4 (&r)[2][4], uint32_t tile, int node, int lane) {
    const int nd = node + ((lane >> 2) & 1);
    const uint32_t qa = tile + (lane >> 4) * KB + nd * 128 + (((lane ^ (lane >> 1 & 4) ^ nd) & 7) << 4);
    const uint4 q0 = ldsm4(qa), q1 = ldsm4(qa + 2 * KB);
    float s[4] = {0.f, 0.f, 0.f, 0.f}, u[4] = {0.f, 0.f, 0.f, 0.f};
    mma16816(s, r[0][0].x, r[0][0].y, r[0][0].z, r[0][0].w, q0.x, q0.y); mma16816(u, r[1][0].x, r[1][0].y, r[1][0].z, r[1][0].w, q0.x, q0.y);
    mma16816(s, r[0][1].x, r[0][1].y, r[0][1].z, r[0][1].w, q0.z, q0.w); mma16816(u, r[1][1].x, r[1][1].y, r[1][1].z, r[1][1].w, q0.z, q0.w);
    mma16816(s, r[0][2].x, r[0][2].y, r[0][2].z, r[0][2].w, q1.x, q1.y); mma16816(u, r[1][2].x, r[1][2].y, r[1][2].z, r[1][2].w, q1.x, q1.y);
    mma16816(s, r[0][3].x, r[0][3].y, r[0][3].z, r[0][3].w, q1.z, q1.w); mma16816(u, r[1][3].x, r[1][3].y, r[1][3].z, r[1][3].w, q1.z, q1.w);
    uint32_t a[4];
    softmax4(s, u, lane, a);
#pragma unroll
    for (int h = 0; h < 2; ++h)
        stsm4(qa + h * 2 * KB, wsum4(a, r[0][2 * h].x, r[0][2 * h].y, r[1][2 * h].x, r[1][2 * h].y), wsum4(a, r[0][2 * h].z, r[0][2 * h].w, r[1][2 * h].z, r[1][2 * h].w),
              wsum4(a, r[0][2 * h + 1].x, r[0][2 * h + 1].y, r[1][2 * h + 1].x, r[1][2 * h + 1].y), wsum4(a, r[0][2 * h + 1].z, r[0][2 * h + 1].w, r[1][2 * h + 1].z, r[1][2 * h + 1].w));
}
__device__ __noinline__ void attention_generic(const Params& p, uint32_t tile, int nl, int node, int lane) {
    const uint32_t qa = tile_chunk(tile, nl, lane);
    const uint4 qv = lds128(qa);
    const float q[8] = {blo(qv.x), bhi(qv.x), blo(qv.y), bhi(qv.y), blo(qv.z), bhi(qv.z), blo(qv.w), bhi(qv.w)};
    float z[8] = {0.f, 0.f, 0.f, 0.f, 0.f, 0.f, 0.f, 0.f};
    float den = 0.f;
#pragma unroll 1
    for (int e = 0; e < p.Ee; e += 32) {
        const bool m = (e + lane < p.Ee) && (__ldg(p.edst + e + lane) == node);
        const int sv = m ? __ldg(p.esrc + e + lane) : 0;
        uint32_t bal = __ballot_sync(0xffffffffu, m);
        while (bal) {
            const int l = __ffs(bal) - 1; bal &= bal - 1;
            const uint4 v = ldg_in(row_ptr(p.x + lane * 16, __shfl_sync(0xffffffffu, sv, l)));
            float c = dot8(q, v);
#pragma unroll
            for (int o = 16; o; o >>= 1) c += __shfl_xor_sync(0xffffffffu, c, o);
            const float pe = expf(c * 0.0625f);
            den += pe;
            fma8(z, pe, v);
        }
    }
    sts128(qa, pack8(z, 1.f / (den + 1e-9f)));
}
__device__ __noinline__ void local_generic(const Params& p, int node0, int w, int lane) {
    float a0[8], a1[8], a2[8], a3[8];
#pragma unroll
    for (int k = 0; k < 8; ++k) { a0[k] = 0.f; a1[k] = 0.f; a2[k] = 0.f; a3[k] = 0.f; }
#pragma unroll 1
    for (int e = 0; e < p.E; e += 32) {
        const int dl = (e + lane < p.E) ? __ldg(p.dst + e + lane) - node0 - w : -1;
        const int k = dl == 0 ? 0 : dl == AW ? 1 : dl == 2 * AW ? 2 : (dl == 3 * AW && w + 3 * AW < NPC) ? 3 : -1;
        const int sv = k >= 0 ? __ldg(p.src + e + lane) : 0;
        uint32_t bal = __ballot_sync(0xffffffffu, k >= 0);
        while (bal) {
            const int l = __ffs(bal) - 1; bal &= bal - 1;
            const int s = __shfl_sync(0xffffffffu, sv, l), kk = __shfl_sync(0xffffffffu, k, l);
            const uint4 v = ldg_sc(p.H + lane * N + s);
            if (kk & 2) { if (kk & 1) fma8(a3, 1.f, v); else fma8(a2, 1.f, v); }
            else        { if (kk & 1) fma8(a1, 1.f, v); else fma8(a0, 1.f, v); }
        }
    }
    const int n = node0 + w;
    red_row(p.out + n * 32 + lane, pack8(a0, __bfloat162float(p.dis[n])));
    red_row(p.out + (n + AW) * 32 + lane, pack8(a1, __bfloat162float(p.dis[n + AW])));
    red_row(p.out + (n + 2 * AW) * 32 + lane, pack8(a2, __bfloat162float(p.dis[n + 2 * AW])));
    if (w + 3 * AW < NPC) red_row(p.out + (n + 3 * AW) * 32 + lane, pack8(a3, __bfloat162float(p.dis[n + 3 * AW])));
}
__device__ __forceinline__ uint32_t hadd2(uint32_t a, uint32_t b) { uint32_t d; asm("add.rn.bf16x2 %0, %1, %2;" : "=r"(d) : "r"(a), "r"(b)); return d; }
__device__ __forceinline__ float plo(uint32_t v) { uint32_t d; asm("prmt.b32 %0, %1, 0, 0x1044;" : "=r"(d) : "r"(v)); return __uint_as_float(d); }
template <int HI, int NR>
__device__ __forceinline__ uint32_t agg_sum(uint32_t w, uint32_t base) {
    uint32_t a, r0, r1, r2, r3;
    if (HI) asm("dp2a.hi.u32.u32 %0, %1, %2, %3;" : "=r"(a) : "r"(w), "r"(0x10000010u), "r"(base));
    else    asm("dp2a.lo.u32.u32 %0, %1, %2, %3;" : "=r"(a) : "r"(w), "r"(0x10000010u), "r"(base));
    if (NR == 2) {
        asm volatile("ldmatrix.sync.aligned.m8n8.x2.shared.b16 {%0,%1}, [%2];" : "=r"(r0), "=r"(r1) : "r"(a));
        return hadd2(r0, r1);
    }
    asm volatile("ldmatrix.sync.aligned.m8n8.x4.shared.b16 {%0,%1,%2,%3}, [%4];" : "=r"(r0), "=r"(r1), "=r"(r2), "=r"(r3) : "r"(a));
    return hadd2(hadd2(r0, r1), hadd2(r2, r3));
}
struct Unit { uint4 a, b; };
__device__ __forceinline__ uint32_t unit_stale(const Unit& x, uint32_t lt) {
    if (CHK1) return ((x.a.x ^ lt) | (x.b.x ^ lt)) & 0xc000u;
    const uint32_t o = x.a.x | x.a.y | x.a.z | x.a.w | x.b.x | x.b.y | x.b.z | x.b.w, a = x.a.x & x.a.y & x.a.z & x.a.w & x.b.x & x.b.y & x.b.z & x.b.w;
    return ((o ^ lt) | (a ^ lt)) & 0xc000u;
}
__device__ __forceinline__ uint32_t agg_tail(float lo, float hi, uint32_t s, const uint4& w, uint32_t base, uint32_t b5, uint32_t b6) {
    if (b5 > 0xffffu) {
        s = hadd2(s, agg_sum<1, 4>(w.z, base));
        if (b6) {
            const uint32_t u = b6 > 0xffffu ? agg_sum<0, 4>(w.w, base) : agg_sum<0, 2>(w.w, base);
            lo += plo(u); hi += bhi(u);
        }
    } else if (b5) s = hadd2(s, agg_sum<1, 2>(w.z, base));
    const float f = bhi(w.w);
    return pack_bf16((lo + plo(s)) * f, (hi + bhi(s)) * f);
}
__device__ __forceinline__ void agg_unit(const Unit& x, uint32_t base, uint32_t stg, uint32_t lt) {
    const uint32_t s0 = hadd2(agg_sum<0, 4>(x.a.x, base), agg_sum<1, 4>(x.a.x, base)), u0 = hadd2(agg_sum<0, 4>(x.b.x, base), agg_sum<1, 4>(x.b.x, base));
    const uint32_t s1 = hadd2(agg_sum<0, 4>(x.a.y, base), agg_sum<1, 4>(x.a.y, base)), u1 = hadd2(agg_sum<0, 4>(x.b.y, base), agg_sum<1, 4>(x.b.y, base));
    const uint32_t s2 = agg_sum<0, 4>(x.a.z, base), u2 = agg_sum<0, 4>(x.b.z, base);
    const uint32_t a5 = __ballot_sync(0xffffffffu, x.a.z > (lt | 0xffffu)), a6 = __ballot_sync(0xffffffffu, x.a.w & 0x3fffu);
    const uint32_t b5 = __ballot_sync(0xffffffffu, x.b.z > (lt | 0xffffu)), b6 = __ballot_sync(0xffffffffu, x.b.w & 0x3fffu);
    const uint32_t oa = agg_tail(plo(s0) + plo(s1), bhi(s0) + bhi(s1), s2, x.a, base, a5, a6);
    const uint32_t ob = agg_tail(plo(u0) + plo(u1), bhi(u0) + bhi(u1), u2, x.b, base, b5, b6);
    asm volatile("stmatrix.sync.aligned.m8n8.x2.shared.b16 [%0], {%1,%2};" :: "r"(stg), "r"(oa), "r"(ob) : "memory");
}

__global__ void __launch_bounds__(NTHR, 1)
fused_kernel(const __grid_constant__ Params p,
             const __grid_constant__ CUtensorMap tmX, const __grid_constant__ CUtensorMap tmWl,
             const __grid_constant__ CUtensorMap tmM, const __grid_constant__ CUtensorMap tmWv,
             const __grid_constant__ CUtensorMap tmR, const __grid_constant__ CUtensorMap tmO,
             const __grid_constant__ CUtensorMap tmG, const __grid_constant__ CUtensorMap tmQ,
             const __grid_constant__ CUtensorMap tmK, const __grid_constant__ CUtensorMap tmV3)
{
    extern __shared__ __align__(1024) unsigned char smem[];
    const uint32_t sb = s32(smem);
    const int tid = threadIdx.x, lane = tid & 31;
    const int warp = __shfl_sync(0xffffffffu, tid >> 5, 0);
    const int cta = blockIdx.x;
    const int node0 = cta * NPC;
    const bool rowcta = cta < RCTA;
    const int slice = cta >> 2, quarter = cta & 3;
    const int nlast = 12 + (quarter == 3);
    const int i0 = (cta >> 3) * 16, j0 = (cta & 7) * 32;
    const uint32_t bars = sb + SM_MISC;
    const uint32_t sS = sb + SM_S, sT = sb + SM_T;

    const bool stage = rowcta && !p.force_eslow;
    auto slow_cta = [&]() { uint32_t a, b; asm volatile("ld.shared.v2.u32 {%0, %1}, [%2];" : "=r"(a), "=r"(b) : "r"(bars + MI_SLOW) : "memory"); return a || b > OVCAP; };
    auto publish = [&](int set) {
        const uint4 dv = lds128(bars + MI_DIS + set * 16);
        uint4 v = lds128(sb + X_IMG + set * 512 + lane * 16);
        const uint4 z = lds128(sb + X_DEF + set * 64 + (lane & 3) * 16);
        if ((lane & 3) == 3) { v.x = __byte_perm(v.x, v.y, 0x5410); v.y = v.w; }
        v.x = __vmaxu2(v.x, z.x); v.y = __vmaxu2(v.y, z.y); v.z = __vmaxu2(v.z, z.z); v.w = __vmaxu2(v.w, z.w);
        if (slow_cta()) v = make_uint4(0, 0, 0, 0);
        const uint32_t lt = list_tag(lds32(bars + MI_EPOCH));
        v.x |= lt; v.y |= lt; v.z |= lt; v.w |= lt;
        if ((lane & 3) == 3) { const uint32_t sel = lane & 16 ? 0x7632 : 0x5410; v.z = __byte_perm(dv.x, dv.y, sel); v.w = __byte_perm(dv.z, dv.w, sel); }
        uint32_t* ip = (uint32_t*)p.idx + (cta * 10 + set) * 128 + lane;
        st_relaxed(ip, __byte_perm(v.x, v.z, 0x5410));      st_relaxed(ip + 32, __byte_perm(v.x, v.z, 0x7632));
        st_relaxed(ip + 64, __byte_perm(v.y, v.w, 0x5410)); st_relaxed(ip + 96, __byte_perm(v.y, v.w, 0x7632));
    };

    if (warp >= AW) {
        const int pw = warp - AW;
        if (elect()) {
            auto init = [&](int b0, int b1, int c) {
#pragma unroll
                for (int b = b0; b < b1; b += 8) mbar_init(bars + b, c);
            };
            if (pw == 0)      { PROF(0); prefetch_map(&tmQ); prefetch_map(&tmK); prefetch_map(&tmX); prefetch_map(&tmWl); init(B_K, B_A, 1); }
            else if (pw == 1) { init(B_A, B_F, 4); mbar_init(bars + B_S, 6); mbar_init(bars + B_VE, GW); mbar_init(bars + B_Z, AW); init(B_HV, B_RV + 8, 1); }
            else if (pw == 2) { init(B_F, B_GO, GW); init(B_FA, B_SENT, 8); mbar_init(bars + B_SENT, LW + 4); }
            else              { init(B_GO, B_Z, 1); init(B_RND, B_RND + 96, 12); mbar_init(bars + B_RND + 96, nlast); }
            asm volatile("fence.mbarrier_init.release.cluster;" ::: "memory");
        }
        bar_arrive(4, LT + 128);
        if (pw) bar_sync(0, GT + 128); else bar_arrive(0, GT + 128);
        auto load_units = [&](const CUtensorMap* tm, int kq, int slot) {
            if (elect()) { mbar_expect(bars + B_K + kq * 8, 4 * UNIT); tma3d(sS + slot * UNIT, tm, kq * 64, bars + B_K + kq * 8); }
        };
        const int v0 = pw ? pw - 2 : 2;
        auto tile_rows = [&](uint2 (&e)[6], int c) {
#pragma unroll
            for (int n = 0; n < 6; ++n) {
                const int v = min(v0 + 3 * n, 15);
                asm volatile("ld.shared.v2.u32 {%0, %1}, [%2];" : "=r"(e[n].x), "=r"(e[n].y) : "r"(bars + MI_ES + ((v >> 2) * 16 + c * 4 + (v & 3)) * 8) : "memory");
            }
        };
        auto stage_tiles = [&](const uint2 (&e)[6], int c) {
            mbar_wait(bars + (c ? B_F + 32 + c * 8 : T0BAR), 0);
            if (elect()) {
#pragma unroll
                for (int n = 0; n < 6; ++n) {
                    const int v = v0 + 3 * n;
                    if (n < 5 || v < 16) {
                        const uint32_t dst = sS + (A_TILES >> (8 * c) & 255) * UNIT + v * 2048, bar = bars + B_A + ((v & 12) + c) * 8;
                        mbar_expect(bar, 2048);
                        tma2d(dst, &tmG, 0, e[n].x & 0xffffu, bar);        tma2d(dst + 512, &tmG, 0, e[n].x >> 16, bar);
                        tma2d(dst + 1024, &tmG, 0, e[n].y & 0xffffu, bar); tma2d(dst + 1536, &tmG, 0, e[n].y >> 16, bar);
                    }
                }
            }
            if (pw == 2 && lane == 0) PROF(45 + c);
        };
        if (pw == 0) {
            if (elect()) {
                mbar_expect(bars + B_QK, 3 * UNIT);
                tma3d(sS + A3 * UNIT, &tmQ, i0, bars + B_QK);
                tma3d(sS + (A3 + 1) * UNIT, &tmK, j0, bars + B_QK);
                if (rowcta) {
#pragma unroll
                    for (int kq = 0; kq < 4; ++kq) mbar_expect(bars + B_K + kq * 8, KB + 4 * UNIT);
#pragma unroll
                    for (int i = 7; i >= 0; --i) {
                        const int kq = (XORD >> (4 * i)) & 3;
                        if ((XORD >> (4 * i)) & 4) tma3d(sS + (kq == 3 ? A4 : 4 * kq) * UNIT, &tmWl, kq * 64, bars + B_K + kq * 8);
                        else tma2d(sT + kq * KB, &tmX, kq * 64, node0, bars + B_K + kq * 8);
                    }
                    PROF(3);
                    prefetch_map(&tmM); prefetch_map(&tmG); prefetch_map(&tmWv); prefetch_map(&tmV3); prefetch_map(&tmR);
                }
            }
        }
        if (pw >= 2 && stage) {
            const uint4 e = ldg_in(p.esrc + (node0 + 32 * (pw - 2) + lane) * 4);
            asm volatile("st.shared.v2.u32 [%0], {%1, %2};" :: "r"(bars + MI_ES + ((pw - 2) * 32 + lane) * 8), "r"(e.x | e.y << 16), "r"(e.z | e.w << 16) : "memory");
        }
        if (pw == 1 && rowcta && lane < 10) sts128(bars + MI_DIS + lane * 16, ldg_in(p.dis + node0 + lane * 8));
        {
            bar_sync(1, GT + 128);
            const int v = tid - AW * 32;
            const float* rp = (const float*)(smem + SM_X) + (v >> 3) * 32 + (((v & 7) * 4 + (v & 24)) & 31);
            const float4 v0 = *(const float4*)rp, v1 = *(const float4*)(rp + 512), v2 = *(const float4*)(rp + 1024), v3 = *(const float4*)(rp + 1536);
            p.M[(i0 + (v >> 3)) * 64 + (j0 >> 2) + (v & 7)] =
                make_uint2(pack_bf16((v0.x + v1.x) + (v2.x + v3.x), (v0.y + v1.y) + (v2.y + v3.y)),
                           pack_bf16((v0.z + v1.z) + (v2.z + v3.z), (v0.w + v1.w) + (v2.w + v3.w)));
            warp_arrive(bars + B_SENT);
        }
        if (pw != 1 && rowcta) {
            uint2 e[4][6];
#pragma unroll
            for (int c = 0; c < 4 - G3; ++c) tile_rows(e[c], c);
            mbar_wait(bars + B_EPO, 0);
            mbar_wait(bars + B_F, 0);
#pragma unroll 1
            for (int c = 0; c < 4 - G3; ++c) {
                if (pw == 0 && c == 0) {
                    mbar_wait(bars + B_CGO, 0);
                    wait_count(p.sync + SY_M, (lds32(bars + MI_EPOCH) + 1) * NCTA);
                    fence_async_gmem();
                    if (lane == 0) PROF(2);
                    load_units(&tmM, 0, A0);
                    if (lane == 0) PROF(39);
                    mbar_wait(bars + B_F + 8, 0);  load_units(&tmM, 1, A1);
                    mbar_wait(bars + B_F + 16, 0); load_units(&tmM, 2, A2);
                    warp_arrive(bars + B_MI);
                    if (lane == 0) PROF(40);
                }
                if (pw == 0 && c == 1) { mbar_wait(bars + B_F + 32, 0); load_units(&tmM, 3, A0); }
                if (stage) stage_tiles(e[0], c);
#pragma unroll
                for (int n = 0; n < 6; ++n) { e[0][n] = e[1][n]; e[1][n] = e[2][n]; if (!G3) e[2][n] = e[3][n]; }
            }
        }
        if (pw == 0) {
            if (rowcta) {
                if (HRW == 1) mbar_wait(bars + B_HR, 0);
                mbar_wait(bars + B_FA, 0);      fence_async_smem();  load_units(&tmWv, 0, A3);
                if (HRW == 2) mbar_wait(bars + B_HR, 0);
                mbar_wait(bars + B_FA + 8, 0);  fence_async_smem();  load_units(&tmWv, 1, A1);
                mbar_wait(bars + B_FA + 16, 0); fence_async_smem();  load_units(&tmWv, 2, A2);
                mbar_wait(bars + B_HR, 0);
                mbar_wait(bars + B_XF, 0);      fence_async_smem();
                if (elect()) {
                    mbar_expect(bars + B_K + 24, 4 * UNIT);
#pragma unroll
                    for (int ks = 0; ks < 4; ++ks) tma3d(sS + (A5 + ks) * UNIT, &tmV3, 192 + ks * 16, bars + B_K + 24);
                }
                if (lane == 0) PROF(5);
            }
        } else if (pw == 1) {
            mbar_wait(bars + B_SENT, 0);
            if (elect()) { PROF(38); red_release(p.sync + SY_M); PROF(1); mbar_arrive(bars + B_CGO); }
            if (VPF && lane < 8) asm volatile("prefetch.global.L2 [%0];" :: "l"(p.wv + (cta * 8 + lane) * 128));
            mbar_wait(bars + B_EPO, 0);
            if (rowcta) {
                mbar_wait(bars + B_HS, 0);
                mbar_wait(bars + B_LF, 0);
                fence_async_smem();
                mbar_wait(bars + B_MI, 0);
                if (HGATE >= 0) mbar_wait(bars + B_K + HGATE * 8, 1);
                uint32_t tn = clk();
#pragma unroll 1
                for (int s = 0; s < 32; s += 2) {
                    wait_clk(tn); tn += HPER;
                    if (elect()) {
                        bulk_store(p.H + s * N + node0, sS + A4 * UNIT + s * 1280, 1280);
                        bulk_store(p.H + (s + 1) * N + node0, sS + A4 * UNIT + s * 1280 + 1280, 1280);
                    }
                }
#pragma unroll 1
                for (int z = cta; z < ER * AW * 16; z += RCTA) {
                    wait_clk(tn); tn += HPER;
                    if (elect()) bulk_store(p.out + ((z & 3) * (UPQ * 16) + (z >> 2) * 4) * 32, sb + X_ZERO, 2048);
                }
                if (elect()) {
                    bulk_commit();
                    asm volatile("cp.async.bulk.wait_group 0;" ::: "memory");
                    PROF(43);
                    fence_async_gmem();
                    red_release(p.sync + SY_H);
                    mbar_arrive(bars + B_HR);
                    PROF(31);
                }
            }
            wait_count(p.sync + SY_H, (lds32(bars + MI_EPOCH) + 1) * RCTA);
            fence_async_gmem();
            warp_arrive(bars + B_HV);
            if (lane == 0) PROF(6);
            const char* hs = (const char*)(p.H + slice * N) - 128;
            auto chunk = [&](int bar, int lo, int hi) {
                if (rowcta && bar) mbar_wait(bars + bar, 0);
                if (bar >= B_FA) fence_async_smem();
                if (lo == 128) { if (lane < 8) sts128(sS + lane * 16, make_uint4(0, 0, 0, 0)); __syncwarp(); }
                if (elect()) { mbar_expect(bars + B_S, hi - lo); bulk_load(sS + lo, hs + lo, hi - lo, bars + B_S); }
            };
            chunk(0, A4 * UNIT, A5 * UNIT);
            chunk(B_FA + 24, 128, 4 * UNIT);
            chunk(B_F + 64, A3 * UNIT, (A3 + 4) * UNIT);
            chunk(B_F + 72, A1 * UNIT, (A1 + 4) * UNIT);
            chunk(B_F + 80, A2 * UNIT, (A2 + 4) * UNIT);
            chunk(B_F + 88, A5 * UNIT, SLICE_END);
            if (lane == 0) PROF(7);
        } else {
            mbar_wait(bars + B_EPO, 0);
            const uint32_t epoch1 = lds32(bars + MI_EPOCH) + 1;
            if (pw == 2) {
                if (rowcta) {
                    uint32_t early = 0;
#pragma unroll
                    for (int r = 0; r < 5; ++r) { const int u = cta * 5 + r; early |= (u - min(u / UPQ, 3) * UPQ < ER * AW) << r; }
                    auto put_r = [&](bool add) {
#pragma unroll 1
                        for (int r = 0; r < 5; ++r) {
                            const int u = cta * 5 + r;
                            if ((early >> r & 1) == add) {
                                if (elect()) {
#pragma unroll
                                    for (int kb = 0; kb < 4; ++kb) {
                                        if (add) tma2d_add(&tmR, sT + kb * KB + r * 2048, kb * 64, u * 16);
                                        else     tma2d_store(&tmR, sT + kb * KB + r * 2048, kb * 64, u * 16);
                                    }
                                }
                                if (RPER && add) wait_clk(clk() + RPER);
                            }
                        }
                        bulk_commit();
                    };
                    mbar_wait(bars + B_R, 0);
                    fence_async_smem();
                    put_r(false);
                    if (elect()) {
                        asm volatile("cp.async.bulk.wait_group 0;" ::: "memory");
                        fence_async_gmem();
                        p.sync[SY_SLOW + cta] = slow_cta();
                        red_release(p.sync + SY_R);
                        PROF(22);
                    }
                    mbar_wait(bars + B_S, 0);
                    put_r(true);
                    bulk_wait_read<0>();
                    if (lane == 0) PROF(41);
                }
                warp_arrive(bars + B_TF);
                wait_count(p.sync + SY_R, epoch1 * RCTA);
                fence_async_gmem();
                warp_arrive(bars + B_RV);
                if (lane == 0) PROF(23);
            } else {
                if (lane == 0) prefetch_map(&tmO);
                mbar_wait(bars + B_XF, 0);
                if (elect()) red_relaxed(p.sync + SY_L);
                wait_count(p.sync + SY_L, epoch1 * NCTA);
                warp_arrive(bars + B_GO);
                if (lane == 0) PROF(42);
                if (cta == 0 && lane < 16) *(volatile uint32_t*)(p.sync + lane * 32) = epoch1;
#pragma unroll 1
                for (int i = 0; i < 13; ++i) {
                    if (i == 2 * ER) mbar_wait(bars + B_RV, 0);
                    mbar_wait(bars + B_RND + i * 8, 0);
                    fence_async_smem();
                    if (elect()) {
                        tma2d_add(&tmO, sb + SM_X + i * 3072, slice * 8, quarter * (UPQ * 16) + i * 192);
                        if (i == 12 && quarter == 3) tma2d_add(&tmO, sb + SM_X + 13 * 3072, slice * 8, 3 * (UPQ * 16) + 13 * 192);
                    }
                    if (lane == 0 && !(i & 1)) PROF(53 + (i >> 1));
                }
                bulk_commit();
                if (lane == 0) PROF(8);
                bulk_wait_read<0>();
                if (lane == 0) PROF(9);
            }
        }
        if (pw < 2) {
            mbar_wait(bars + B_EPO, 0);
            mbar_wait(bars + B_XF, 0);
            const int novf = min(lds32(bars + MI_NOVF), (uint32_t)OVCAP);
#pragma unroll 1
            for (int o = 12 * pw; o < novf; o += 24) {
                const int n = min(novf - o, 12);
                uint32_t w = lds32(bars + MI_OVF + (o + min(lane, n - 1)) * 4);
                int rk = 0;
#pragma unroll 1
                for (int j = 0; j < n; ++j) { const uint32_t y = __shfl_sync(0xffffffffu, w, j); rk += y < w || (y == w && j < lane); }
                if (lane < n) sts32(bars + MI_OVF + (o + rk) * 4, w);
                __syncwarp();
                w = lds32(bars + MI_OVF + (o + min(lane, n - 1)) * 4);
                const uint32_t more = __ballot_sync(0xffffffffu, (((__shfl_down_sync(0xffffffffu, w, 1) ^ w) >> 14) == 0) & (lane + 1 < n));
                const uint32_t f = __ldg((const unsigned short*)p.dis + (w >> 14)) * 0x10001u;
                mbar_wait(bars + B_HV, 0);
                uint4 v[12];
#pragma unroll
                for (int i = 0; i < 12; i += 3) {
                    if (i < n) {
#pragma unroll
                        for (int j = i; j < i + 3; ++j) {
                            const uint32_t s = __shfl_sync(0xffffffffu, w, j) & 0x3fffu;
                            v[j] = make_uint4(0, 0, 0, 0);
                            if (j < n) v[j] = ldg_sc(p.H + lane * N + s);
                        }
#pragma unroll
                        for (int j = i; j < i + 3; ++j) {
                            const uint32_t fj = __shfl_sync(0xffffffffu, f, j);
                            v[j] = make_uint4(hmul2(v[j].x, fj), hmul2(v[j].y, fj), hmul2(v[j].z, fj), hmul2(v[j].w, fj));
                            if (j && (more >> (j - 1) & 1)) v[j] = make_uint4(hadd2(v[j].x, v[j - 1].x), hadd2(v[j].y, v[j - 1].y), hadd2(v[j].z, v[j - 1].z), hadd2(v[j].w, v[j - 1].w));
                        }
                    }
                }
                mbar_wait(bars + B_RV, 0);
                const uint32_t go = __ballot_sync(0xffffffffu, lane < n && !ld_relaxed(p.sync + SY_SLOW + (w >> 14) / NPC)) & ~more;
#pragma unroll
                for (int j = 0; j < 12; ++j)
                    if (go >> j & 1) red_row(p.out + (__shfl_sync(0xffffffffu, w, j) >> 14) * 32 + lane, v[j]);
            }
            if (lane == 0) PROF(pw ? 48 : 44);
        }
    } else {
        const int g = lane >> 2, t = lane & 3;
        const int wi = warp < GW ? warp + LW : warp - GW;
        Unit x0, x1;
        const uint4* ip;
        auto fetch = [&](Unit& x, int j) { x.a = ld_relaxed4(ip + j * 64); x.b = ld_relaxed4(ip + j * 64 + 32); };
        auto fetch0 = [&]() { int l = lane; asm volatile("" : "+r"(l)); ip = p.idx + quarter * (UPQ * 64) + l; fetch(x0, wi); };
        if (warp < GW) {
            const int wg = warp >> 2, w4 = warp & 3;
            uint32_t h[20];
            if (rowcta) {
#pragma unroll
                for (int j = 0; j < 10; ++j) h[j] = __ldg((const uint32_t*)p.dis + (node0 >> 1) + 4 * j + t);
            }
            bar_sync(0, GT + 128);
            {
                float* red = (float*)(smem + SM_X);
                const int cw = (w4 - wg * (MW == 1 ? 1 : MW == 2 ? 2 : 0)) & 3;
                if (cw < MW) {
                    const uint32_t qa = sS + A3 * UNIT + wg * 2048 + (lane & 15) * 128 + (((lane >> 4) ^ (lane & 7)) << 4);
                    const uint32_t ka = sS + (A3 + 1) * UNIT + wg * 4096 + (cw * (32 / MW) + (lane & 7)) * 128 + (((lane >> 3) ^ (lane & 7)) << 4);
                    mbar_wait(bars + B_QK, 0);
                    __syncwarp();
                    if (tid == 0) PROF(33);
                    const uint4 a0 = ldsm4(qa), a1 = ldsm4(qa ^ 32), a2 = ldsm4(qa ^ 64), a3 = ldsm4(qa ^ 96);
                    uint4 bb[4 / MW][2];
#pragma unroll
                    for (int nb = 0; nb < 4 / MW; ++nb) { bb[nb][0] = ldsm4(ka + nb * 1024); bb[nb][1] = ldsm4((ka ^ 64) + nb * 1024); }
#pragma unroll
                    for (int nb = 0; nb < 4 / MW; ++nb) {
                        const uint4 b0 = bb[nb][0], b1 = bb[nb][1];
                        float c[4] = {0.f, 0.f, 0.f, 0.f}, e[4] = {0.f, 0.f, 0.f, 0.f};
                        mma16816(c, a0.x, a0.y, a0.z, a0.w, b0.x, b0.y); mma16816(e, a1.x, a1.y, a1.z, a1.w, b0.z, b0.w);
                        mma16816(c, a2.x, a2.y, a2.z, a2.w, b1.x, b1.y); mma16816(e, a3.x, a3.y, a3.z, a3.w, b1.z, b1.w);
                        float* rp = red + (wg * 16 + g) * 32 + (((cw * (4 / MW) + nb + g) & 3) * 8) + 2 * t;
                        *(float2*)rp         = make_float2(c[0] + e[0], c[1] + e[1]);
                        *(float2*)(rp + 256) = make_float2(c[2] + e[2], c[3] + e[3]);
                    }
                }
                bar_arrive(1, GT + 128);
            }
            if (rowcta) {
                float d[40];
                const uint32_t uw = sS + wg * UNIT, fb = bars + B_F;
                fence_async_smem();
                mbar_wait(bars + B_SENT, 0);
                if (tid == 0) PROF(35);
                gemm_quarter<0>(d, uw + A0 * UNIT, sT, bars + B_K, 0);
                if (tid == 0) PROF(10);
                gemm_quarter<1>(d, uw + A1 * UNIT, sT, bars + B_K, 0, fb);
                gemm_quarter<2>(d, uw + A2 * UNIT, sT, bars + B_K, 0, fb + 8);
                gemm_quarter<3>(d, uw + A4 * UNIT, sT, bars + B_K, 0, fb + 16);
                wg_wait<0>(); warp_arrive(fb + 24);
                if (tid == 0) PROF(11);
#pragma unroll
                for (int j = 9; j >= 0; --j) {
                    const float s0 = blo(h[j]), s1 = bhi(h[j]);
                    h[2 * j + 1] = pack_bf16(d[4 * j + 2] * s0, d[4 * j + 3] * s1);
                    h[2 * j]     = pack_bf16(d[4 * j] * s0, d[4 * j + 1] * s1);
                }
                mbar_wait(fb + 24, 0);
                __syncwarp();
                {
                    const uint32_t sa = sS + A4 * UNIT + warp * 2560 + (lane & 8) * 160 + (lane >> 4) * 128 + (lane & 7) * 16;
#pragma unroll
                    for (int i = 0; i < 5; ++i) stsm4t(sa + i * 256, h[4 * i], h[4 * i + 1], h[4 * i + 2], h[4 * i + 3]);
                }
                warp_arrive(bars + B_HS);
                if (QLF) mbar_wait(bars + B_LF, 0);
                uint4 e3 = make_uint4(0, 0, 0, 0);
                if (G3 && stage) e3 = ldg_in(p.esrc + (node0 + 16 * wg + 12 + w4) * 4);
                gemm_quarter<0>(d, uw + A0 * UNIT, sT, bars + B_K, 1);
                if (tid == 0) PROF(12);
                gemm_quarter<1>(d, uw + A1 * UNIT, sT, bars + B_K, 1, fb + 32);
                gemm_quarter<2>(d, uw + A2 * UNIT, sT, bars + B_K, 1, fb + 40);
                mbar_wait(bars + B_LF, 0);
                const uint32_t ebad = lds32(bars + MI_EBAD);
                gemm_quarter<3>(d, uw + A0 * UNIT, sT, bars + B_K, 1, fb + 48);
                if (tid == 0) PROF(13);
                wg_wait<0>(); warp_arrive(fb + 56);
                if (tid == 0) PROF(14);
                pack_acc(h, d);
                mbar_wait(fb + 32 + wg * 8, 0);
                __syncwarp();
                store_tile(h, sT, wg, w4, lane);
                warp_arrive(bars + B_Q);
                auto stage3 = [&]() {
                    mbar_wait(fb + 56, 0);
                    if (G3 && stage && elect()) {
                        const uint32_t dst = uw + A0 * UNIT + w4 * 2048, bar = bars + B_A + (4 * wg + 3) * 8;
                        mbar_expect(bar, 2048);
                        tma2d(dst, &tmG, 0, e3.x, bar);        tma2d(dst + 512, &tmG, 0, e3.y, bar);
                        tma2d(dst + 1024, &tmG, 0, e3.z, bar); tma2d(dst + 1536, &tmG, 0, e3.w, bar);
                    }
                };
                const uint32_t rows = uw + (w4 & 1) * 4096 + (lane & 4) * 512 + (lane & 8) * 64 + (((lane ^ (lane >> 2 & 4)) & 7) << 4);
#pragma unroll AUNR
                for (int c2 = 0; c2 < 4; c2 += 2) {
                    const int c = (w4 >> 1) + c2;
                    const int n = 16 * wg + 4 * c + 2 * (w4 & 1);
                    if (stage) mbar_wait(bars + B_A + (4 * wg + c) * 8, 0);
                    if (tid == 0) PROF(c ? 50 : 15);
                    if (tid == 96) PROF(c == 1 ? 51 : 52);
                    if (!ebad) {
                        const uint32_t ra = rows + (A_TILES >> (8 * c) & 255) * UNIT;
                        uint4 r[2][4];
#pragma unroll
                        for (int kb = 0; kb < 4; ++kb) { r[0][kb] = ldsm4(ra + kb * 128); r[1][kb] = ldsm4(ra + 1024 + kb * 128); }
                        warp_arrive(bars + B_FA + c * 8);
                        if (c2 == 0) { stage3(); mbar_wait(bars + B_Q, 0); }
                        __syncwarp();
                        attention_frags(r, sT, n, lane);
                    } else {
                        warp_arrive(bars + B_FA + c * 8);
                        if (c < 2) stage3();
                        mbar_wait(bars + B_Q, 0);
                        attention_generic(p, sT, n, node0 + n, lane); attention_generic(p, sT, n + 1, node0 + n + 1, lane);
                    }
                }
                fence_async_smem();
                warp_arrive(bars + B_Z);
                if (tid == 0) PROF(16);
                mbar_wait(bars + B_K, 0);
                if (tid == 0) PROF(17);
                gemm_quarter<0>(d, uw + A3 * UNIT, sT, bars + B_Z, 0);
                gemm_quarter<1>(d, uw + A1 * UNIT, sT, bars + B_K, 0, fb + 64);
                gemm_quarter<2>(d, uw + A2 * UNIT, sT, bars + B_K, 0, fb + 72);
                bool early = false;
                if (EFETCH == 1) { early = mbar_test(bars + B_GO, 0); if (early) fetch0(); }
                {
                    mbar_wait(bars + B_K + 24, 0);
                    __syncwarp();
                    const uint32_t a = desc_lo(sS + A5 * UNIT + wg * 2048), b = desc_lo(sT) + ((3 * KB) >> 4);
                    wg_fence();
                    wgmma80<false>(d, a, b);            wg_commit(); wg_wait<1>(); warp_arrive(fb + 80);
                    wgmma80<false>(d, a + 512, b + 2);  wg_commit(); wg_wait<1>(); warp_arrive(fb + 88);
                    if (EFETCH == 2) { early = mbar_test(bars + B_GO, 0); if (early) fetch0(); }
                    wgmma80<false>(d, a + 1024, b + 4);
                    wgmma80<false>(d, a + 1536, b + 6); wg_commit();
                    if (EFETCH == 3) { early = mbar_test(bars + B_GO, 0); if (early) fetch0(); }
                }
                wg_wait<0>(); warp_arrive(bars + B_VE);
                if (tid == 0) PROF(18);
                pack_acc(h, d);
                mbar_wait(wg == 3 ? bars + B_VE : fb + 64 + wg * 8, 0);
                __syncwarp();
                store_tile(h, sT, wg, w4, lane);
                warp_arrive(bars + B_R);
                if (!early) { mbar_wait(bars + B_GO, 0); fetch0(); }
                if (tid == 0) PROF(19);
            } else {
                mbar_wait(bars + B_GO, 0);
                fetch0();
            }
        } else {
            const int lw = warp - GW, tl = tid - GT;
            const uint32_t epoch = ld_relaxed(p.sync + (cta & 15) * 32);
            uint32_t dd[5], ss[5];
            {
                const int e0 = cta * p.chunk, e1 = min(e0 + p.chunk, p.Efast);
#pragma unroll
                for (int k = 0; k < 5; ++k) { dd[k] = (RCTA + (lane & 1)) * NPC; ss[k] = 0; }
#pragma unroll
                for (int k = 0; k < 2; ++k) {
                    const int e = e0 + 2 * (tl + k * LT);
                    if (e < e1) {
                        const int2 d = __ldg((const int2*)(p.dst + e)), s = __ldg((const int2*)(p.src + e));
                        dd[2 * k] = d.x; dd[2 * k + 1] = d.y; ss[2 * k] = s.x; ss[2 * k + 1] = s.y;
                    }
                }
                const int e = e0 + 4 * LT + tl;
                if (e < e1) { dd[4] = __ldg(p.dst + e); ss[4] = __ldg(p.src + e); }
            }
            int4 ed = make_int4(0, 0, 0, 0), es = make_int4(0, 0, 0, 0);
            if (stage) {
                if (tl < NPC) ed = __ldg((const int4*)p.edst + node0 + tl);
                es = __ldg((const int4*)p.esrc + node0 + 64 + 2 * lw + (lane >> 4));
            }
            {
                const uint32_t lo = (tl & 3) * 0x40004000u, hi = (NPC * 2 + (cta & 7)) * 0x010101u;
#pragma unroll
                for (int r = 0; r < 2; ++r) {
                    sts128(sb + X_OUT + (tl + r * LT) * 16, make_uint4(lo, lo, (lo & 0xffffu) | hi << 16, hi));
                    sts128(sb + X_IMG + (tl + r * LT) * 16, make_uint4(0, 0, 0, 0));
                }
            }
            if (tl < 32) sts128(bars + MI_PCNT + tl * 16, make_uint4(0, 0, 0, 0));
            if (tl == 32) { sts32(bars + MI_SLOW, p.force_slow); sts32(bars + MI_EBAD, p.force_eslow); sts32(bars + MI_NOVF, 0); sts32(bars + MI_FLAGS, 0); }
            bar_sync(2, LT);
            if (tl == 0) PROF(34);
            const int zero = lds32(bars + MI_PCNT + 127 * 4);
            uint32_t q[5], nx = 0, ox = 0;
            {
                uint32_t c[5];
#pragma unroll
                for (int k = 0; k < 5; ++k) {
                    dd[k] += zero;
                    c[k] = dd[k] / NPC;
                    q[k] = atoms_add(bars + MI_PCNT + c[k] * 4, c[k] < RCTA);
                }
                if (tl == 0) PROF(36);
#pragma unroll
                for (int k = 0; k < 5; ++k) {
                    const uint32_t w = (((dd[k] - c[k] * NPC) * 8 + (ss[k] & 7u)) << 14) + ss[k] + 8;
                    uint32_t sl = (q[k] >> 2) + (SROT ? (c[k] >> 3) & 3u : 0u);
                    if (SROT) sl = min(sl, sl - 5);
                    const uint32_t ca = sb + X_OUT + c[k] * 64 + ((q[k] + (c[k] >> 1)) & 3u) * 16 + sl;
                    if (q[k] < CELLN) { sts16(ca + sl, w); asm volatile("st.shared.u8 [%0 + 10], %1;" :: "r"(ca), "r"(w >> 16) : "memory"); }
                    nx += q[k] >= CELLN;
                }
                if (nx) ox = atoms_add(bars + MI_NOVF, nx);
                const int nz = node0 + tl + zero;
                if (stage && tl < NPC && ((ed.x != nz) | (ed.y != nz) | (ed.z != nz) | (ed.w != nz))) sts32(bars + MI_FLAGS, W_EBAD);
            }
            if (tl == 0) PROF(37);
            bar_sync(4, LT + 128);
            if (tl == 0) PROF(24);
            const uint32_t tag = ((epoch + zero) % 31u + 1u) << 27;
            {
                const uint32_t fl = lds32(bars + MI_FLAGS) | tag | (lds32(bars + MI_NOVF) > OVCAP / 2 ? W_OVF : 0u);
                uint4* const gp = p.cells + ((tl >> 2) * NCTA + cta) * 4 + (tl & 3);
#pragma unroll
                for (int r = 0; r < 2; ++r) {
                    uint4 w = lds128(sb + X_OUT + (tl + r * LT) * 16);
                    w.w |= fl;
                    if (r == 0 || tl + LT < RCTA * 4) gp[r * (LT / 4) * NCTA * 4] = w;
                }
            }
            warp_arrive(bars + B_SENT);
            if (tl == 0) { sts32(bars + MI_EPOCH, epoch); mbar_arrive(bars + B_EPO); }
            if (tl == 0) PROF(25);
#pragma unroll
            for (int k = 0; k < 5; ++k) {
                if (q[k] >= CELLN) sts32(bars + MI_OVF + min(ox, (uint32_t)OVCAP - 1) * 4, dd[k] << 14 | ss[k]);
                ox += q[k] >= CELLN;
            }
            uint4 r[4][2];
            auto load_rows = [&]() {
                if (stage) {
                    const char* xl = p.x + (lane & 15) * 16;
                    const char* r0 = row_ptr(xl, es.x); const char* r1 = row_ptr(xl, es.y); const char* r2 = row_ptr(xl, es.z); const char* r3 = row_ptr(xl, es.w);
                    r[0][0] = ldg_in(r0); r[0][1] = ldg_in(r0 + 256); r[1][0] = ldg_in(r1); r[1][1] = ldg_in(r1 + 256);
                    r[2][0] = ldg_in(r2); r[2][1] = ldg_in(r2 + 256); r[3][0] = ldg_in(r3); r[3][1] = ldg_in(r3 + 256);
                }
            };
            auto attend = [&]() {
                mbar_wait(bars + B_Q, 0);
                __syncwarp();
                if (!lds32(bars + MI_EBAD)) attention_chunks(r, sT, 64 + 2 * lw, lane);
                else { attention_generic(p, sT, 64 + 2 * lw, node0 + 64 + 2 * lw, lane); attention_generic(p, sT, 65 + 2 * lw, node0 + 65 + 2 * lw, lane); }
                fence_async_smem();
                warp_arrive(bars + B_Z);
                if (tl == 0) PROF(32);
            };
            if (rowcta) {
                mbar_wait(bars + B_SENT, 0);
                if (tl == LT - 1) sts32(sb + X_TAB + NPC * 64, 64);
                if (tl < 128) sts128(sb + X_ZERO + tl * 16, make_uint4(0, 0, 0, 0));
                uint4 c0, c1;
                const uint4* cp = p.cells + cta * (NCTA * 4) + tl;
                if (RGATE == 2) mbar_wait(bars + B_MI, 0);
                mbar_wait(bars + B_CGO, 0);
#pragma unroll 1
                for (int it = 0;; ++it) {
                    c0 = ld_relaxed4(cp); c1 = ld_relaxed4(cp + LT);
                    if (!__any_sync(0xffffffffu, ((c0.w ^ tag) | (c1.w ^ tag)) >> 27) || it >= SPIN_LIMIT) break;
                }
                if (tl == 0) PROF(26);
                if (RGATE == 1) mbar_wait(bars + B_MI, 0);
                if ((c0.w | c1.w) & W_OVF)  sts32(bars + MI_SLOW, 1);
                if ((c0.w | c1.w) & W_EBAD) sts32(bars + MI_EBAD, 1);
                uint32_t w[10] = {__byte_perm(c0.x, c0.z, 0x6610), __byte_perm(c0.x, c0.z, 0x7732), __byte_perm(c0.y, c0.w, 0x4410), __byte_perm(c0.y, c0.w, 0x5532), __byte_perm(c0.z, c0.w, 0x6610),
                                  __byte_perm(c1.x, c1.z, 0x6610), __byte_perm(c1.x, c1.z, 0x7732), __byte_perm(c1.y, c1.w, 0x4410), __byte_perm(c1.y, c1.w, 0x5532), __byte_perm(c1.z, c1.w, 0x6610)};
                {
                    uint32_t c[10];
#pragma unroll
                    for (int m = 0; m < 10; ++m) {
                        const uint32_t a = (w[m] >> 12) & 0xffcu;
                        c[m] = atoms_add(sb + X_CNT + a, a < NPC * 32);
                        w[m] = (w[m] & 0x3fffu) + (a << 15);
                    }
#pragma unroll
                    for (int m = 0; m < 10; ++m) w[m] += (c[m] > 7 ? 0x20000u : c[m]) << 14;
                }
                bar_sync(2, LT);
                if (tl == 0) { mbar_arrive(bars + B_LF); PROF(27); }
                if (lw < 3) {
                    const int d0 = min(tl, NPC - 8 + (tl & 7));
                    const int dl = d0 ^ ((d0 >> 3) & 1);
                    const uint4 n0 = lds128(sb + X_CNT + dl * 32), n1 = lds128(sb + X_CNT + dl * 32 + 16);
                    uint32_t pk = min(n0.x, 8u) + (min(n0.y, 8u) << 4) + (min(n0.z, 8u) << 8) + (min(n0.w, 8u) << 12) +
                                  (min(n1.x, 8u) << 16) + (min(n1.y, 8u) << 20) + (min(n1.z, 8u) << 24) + (min(n1.w, 8u) << 28);
                    pk = __funnelshift_r(pk, pk, 4 * lane);
                    uint32_t du = 0xf0000000u, ru = 0, b[8] = {0, 0, 0, 0, 0, 0, 0, 0};
                    auto code2 = [&](uint32_t b0, uint32_t b1) {
                        return __byte_perm(__float_as_uint(__uint_as_float(b0) * 8388608.f), __float_as_uint(__uint_as_float(b1) * 8388608.f), 0x7632);
                    };
                    uint32_t ta = (lane + 7) * 8;
                    auto pass_on = [&]() {
                        ru = __shfl_sync(0xffffffffu, ru, lane + 1, 8);
                        const uint32_t t0 = (code2(b[0], b[2]) >> 7) + code2(b[1], b[3]) * 2, t1 = (code2(b[4], b[6]) >> 7) + code2(b[5], b[7]) * 2;
                        asm volatile("st.shared.v2.u32 [%0], {%1, %2};" :: "r"(sb + X_TAB + ((dl * 64) | (ta & 56))), "r"(t0), "r"(t1) : "memory");
                        ta += 8;
                    };
                    auto take = [&](uint32_t& m, uint32_t& bit, uint32_t n, int c) {
                        asm("{\n.reg .pred p;\n.reg .b32 u;\nsetp.gt.u32 p, %2, %3;\nadd.u32 u, %0, -1;\nlop3.b32 %1, %0, u, 0, 0x30;\n@p and.b32 %0, %0, u;\n}"
                            : "+r"(m), "=r"(bit) : "r"(n), "r"(c));
                    };
#pragma unroll 1
                    for (int k = 0; k < 8; ++k) {
                        const uint32_t n = pk & 15u;
                        const bool big = __any_sync(0xffffffffu, n > 6);
                        pk >>= 4;
                        pass_on();
                        const uint32_t fr = ~(du | ru);
                        uint32_t m = fr;
#pragma unroll
                        for (int c = 0; c < 6; ++c) take(m, b[c], n, c);
                        if (big) { take(m, b[6], n, 6); take(m, b[7], n, 7); }
                        du |= m ^ fr;
                        ru |= m ^ fr;
                    }
                    pass_on();
                    sts32(sb + X_RU + d0 * 4, ru);
                }
                if (tl == 0) PROF(49);
                if (LGATE >= 0) { mbar_wait(bars + B_MI, 0); mbar_wait(bars + B_K + LGATE * 8, 1); }
                load_rows();
                bar_sync(2, LT);
                if (tl == 0) PROF(28);
                const int v = LT - 1 - tl;
                if (lw >= 6 && v < 40) {
                    const uint4 b = lds128(sb + X_RU + (v >> 2) * 32), e = lds128(sb + X_RU + (v >> 2) * 32 + 16);
                    const uint32_t f2 = b.x & b.y & b.z & b.w;
                    const uint32_t s0 = (f2 & e.x) | (~f2 & b.x), s1 = (f2 & e.y) | (~f2 & b.y), s2 = (f2 & e.z) | (~f2 & b.z);
                    const uint32_t f1 = s0 & s1, f0 = (f1 & s2) | (~f1 & s0);
                    uint32_t u[4];
#pragma unroll
                    for (int k = 0; k < 4; ++k) {
                        const int sh = (v & 3) * 8 + 2 * k;
                        u[k] = ((((f0 >> sh) & 3u) * 0x8001u) & 0x10001u) + ((((f1 >> sh) & 3u) * 0x10002u) & 0x20002u) + ((((f2 >> sh) & 3u) * 0x20004u) & 0x40004u);
                    }
                    sts128(sb + X_DEF + v * 16, make_uint4(u[0], u[1], u[2], u[3]));
                }
                {
                    uint32_t rd[10];
#pragma unroll
                    for (int m = 0; m < 10; ++m) asm volatile("ld.shared.u8 %0, [%1];" : "=r"(rd[m]) : "r"(sb + X_TAB + min(w[m] >> 14, NPC * 64u)) : "memory");
#pragma unroll
                    for (int m = 0; m < 10; ++m) {
                        rd[m] -= 1;
                        if (rd[m] < 48) sts16(sb + X_IMG + ((w[m] >> 14) & ~63u) + min(rd[m], 31u) * 2, w[m] & 0x3fffu);
                        w[m] |= rd[m] & 0x80000000u;
                    }
                    if (__any_sync(0xffffffffu, (int)(w[0] | w[1] | w[2] | w[3] | w[4] | w[5] | w[6] | w[7] | w[8] | w[9]) < 0)) {
                        uint32_t n = 0;
#pragma unroll
                        for (int m = 0; m < 10; ++m) n += w[m] >> 31;
                        uint32_t o = atoms_add(bars + MI_NOVF, n);
#pragma unroll
                        for (int m = 0; m < 10; ++m) {
                            if ((int)w[m] < 0) sts32(bars + MI_OVF + min(o, (uint32_t)OVCAP - 1) * 4, ((w[m] >> 6) & 0x1fc000u) + (w[m] & 0x3fffu) + (node0 * 16384 - 8));
                            o += w[m] >> 31;
                        }
                    }
                }
                bar_sync(2, LT);
                if (tl == 0) PROF(29);
#pragma unroll 1
                for (int set = lw; set < 10; set += lw >= 3 && lw < 5 ? 5 : 10) publish(set);
            }
            warp_arrive(bars + B_XF);
            if (tl == 0) PROF(30);
            if (rowcta) attend();
            mbar_wait(bars + B_GO, 0);
            fetch0();
        }
        const uint32_t stg = sb + SM_X + (lane & 15) * 16;
        const uint32_t lt = list_tag(lds32(bars + MI_EPOCH)), base = sS - (lt & 0xffffu) * 16;
        const int nu = UPQ + (quarter == 3);
        int u = wi;
        auto unit = [&](Unit& c, Unit& n) {
#pragma unroll 1
            for (int it = 0;; ++it) {
                if (!__any_sync(0xffffffffu, unit_stale(c, lt) > (it < SPIN_LIMIT ? 0u : 0xffffu))) break;
                fetch(c, u);
            }
            if (u >= 4 * AW) { mbar_wait(bars + B_TF, 0); __syncwarp(); }
            if (u + AW < nu) fetch(n, u + AW);
            agg_unit(c, base, stg + u * 256, lt);
            warp_arrive(bars + B_RND + min((u * 171) >> 11, 12) * 8);
            u += AW;
        };
        mbar_wait(bars + B_S, 0);
        if (rowcta) mbar_wait(bars + B_VE, 0);
        __syncwarp();
        if (tid == 0) PROF(20);
        if (tid == GT) PROF(4);
#pragma unroll 1
        for (;;) {
            unit(x0, x1);
            if (u >= nu) break;
            unit(x1, x0);
            if (u >= nu) break;
        }
        if (WPROF) { if (lane == 0) PROF(24 + wi); } else if (tid == 0) PROF(21);
        if (rowcta && slow_cta()) { mbar_wait(bars + B_RV, 0); local_generic(p, node0, wi, lane); }
    }
    PROF_FLUSH();
}

typedef CUresult (*EncodeFn)(CUtensorMap*, CUtensorMapDataType, cuuint32_t, void*, const cuuint64_t*, const cuuint64_t*,
                             const cuuint32_t*, const cuuint32_t*, CUtensorMapInterleave, CUtensorMapSwizzle,
                             CUtensorMapL2promotion, CUtensorMapFloatOOBfill);

static void make_map(EncodeFn enc, CUtensorMap* m, const void* ptr, int rows, int box_cols, int box_rows) {
    cuuint64_t dims[2] = {(cuuint64_t)D, (cuuint64_t)rows};
    cuuint64_t strides[1] = {(cuuint64_t)D * 2};
    cuuint32_t box[2] = {(cuuint32_t)box_cols, (cuuint32_t)box_rows};
    cuuint32_t es[2] = {1u, 1u};
    enc(m, CU_TENSOR_MAP_DATA_TYPE_BFLOAT16, 2, const_cast<void*>(ptr), dims, strides, box, es, CU_TENSOR_MAP_INTERLEAVE_NONE,
        box_cols == 64 ? CU_TENSOR_MAP_SWIZZLE_128B : CU_TENSOR_MAP_SWIZZLE_NONE,
        box_cols == 64 ? PROMO : CU_TENSOR_MAP_L2_PROMOTION_NONE, CU_TENSOR_MAP_FLOAT_OOB_FILL_NONE);
}
static void make_map3(EncodeFn enc, CUtensorMap* m, const void* ptr, int rows, int box_rows) {
    cuuint64_t dims[3] = {64, (cuuint64_t)rows, 4};
    cuuint64_t strides[2] = {(cuuint64_t)D * 2, 128};
    cuuint32_t box[3] = {64u, (cuuint32_t)box_rows, 4u};
    cuuint32_t es[3] = {1u, 1u, 1u};
    enc(m, CU_TENSOR_MAP_DATA_TYPE_BFLOAT16, 3, const_cast<void*>(ptr), dims, strides, box, es, CU_TENSOR_MAP_INTERLEAVE_NONE,
        CU_TENSOR_MAP_SWIZZLE_128B, CU_TENSOR_MAP_L2_PROMOTION_L2_256B, CU_TENSOR_MAP_FLOAT_OOB_FILL_NONE);
}

}

extern "C" void kernel_launch(void* const* d_in, const int* in_sizes, int n_in, void* d_out, int out_size) {
    using namespace gk;
    (void)n_in; (void)out_size;
    static EncodeFn enc = nullptr;
    static void *m_ptr, *cells_ptr, *sync_ptr, *h_ptr, *idx_ptr;
    if (!enc) {
        void* fn = nullptr;
        cudaDriverEntryPointQueryResult qr;
        cudaGetDriverEntryPoint("cuTensorMapEncodeTiled", &fn, cudaEnableDefault, &qr);
        enc = (EncodeFn)fn;
        cudaGetSymbolAddress(&m_ptr, g_M);
        cudaGetSymbolAddress(&cells_ptr, g_cells);
        cudaGetSymbolAddress(&sync_ptr, g_sync);
        cudaGetSymbolAddress(&h_ptr, g_H);
        cudaGetSymbolAddress(&idx_ptr, g_idx);
        cudaFuncSetAttribute(fused_kernel, cudaFuncAttributeMaxDynamicSharedMemorySize, SM_ALLOC);
    }
    if (in_sizes[5] != N || in_sizes[0] != N * D) return;
    Params p;
    p.src  = (const int*)d_in[1];
    p.dst  = (const int*)d_in[2];
    p.esrc = (const int*)d_in[3];
    p.edst = (const int*)d_in[4];
    p.sync = (uint32_t*)sync_ptr;
    p.x    = (const char*)d_in[0];
    p.dis  = (const __nv_bfloat16*)d_in[5];
    p.wv   = (const char*)d_in[9];
    p.cells = (uint4*)cells_ptr;
    p.H    = (uint4*)h_ptr;
    p.idx  = (uint4*)idx_ptr;
    p.M    = (uint2*)m_ptr;
    p.out  = (uint4*)d_out;
    p.E  = in_sizes[1];
    p.Ee = in_sizes[3];
    p.chunk = (((p.E + NCTA - 1) / NCTA) + 1) & ~1;
    p.force_slow  = (p.chunk > 5 * LT || (p.E & 1)) ? 1 : 0;
    p.force_eslow = (p.Ee != 4 * N) ? 1 : 0;
    p.Efast = p.force_slow ? 0 : p.E;

    CUtensorMap tmX, tmWl, tmM, tmWv, tmR, tmO, tmG, tmQ, tmK, tmV3;
    make_map(enc, &tmX, d_in[0], N, 64, NPC);
    make_map3(enc, &tmWl, d_in[6], D, 64);
    make_map3(enc, &tmM, m_ptr, D, 64);
    make_map3(enc, &tmWv, d_in[9], D, 64);
    make_map(enc, &tmR, d_out, N, 64, 16);
    make_map(enc, &tmO, d_out, N, 8, 192);
    make_map(enc, &tmG, d_in[0], N, 256, 1);
    make_map3(enc, &tmQ, d_in[7], D, 16);
    make_map3(enc, &tmK, d_in[8], D, 32);
    make_map3(enc, &tmV3, d_in[9], D, 16);
    fused_kernel<<<NCTA, NTHR, SM_ALLOC, cudaStreamPerThread>>>(p, tmX, tmWl, tmM, tmWv, tmR, tmO, tmG, tmQ, tmK, tmV3);
}
```

```cpp
#include <cuda_runtime.h>
#include <cuda_bf16.h>
#include <cuda.h>
#include <stdint.h>

#define PROFILE 0

namespace gk {

constexpr int N      = 10000;
constexpr int D      = 256;
constexpr int NPC    = 80;
constexpr int NCTA   = 128;
constexpr int RCTA   = N / NPC;
constexpr int NSET   = N / 8;
constexpr int GW     = 16;
constexpr int LW     = 8;
constexpr int AW     = GW + LW;
constexpr int GT     = GW * 32, LT = LW * 32;
constexpr int NTHR   = (AW + 4) * 32;
constexpr int UPQ    = 156;
constexpr int OVCAP  = 128;
#define SPINB 18
constexpr int SPIN_LIMIT = 1 << SPINB;

constexpr int KB      = NPC * 128;
constexpr int UNIT    = 8192;
constexpr int SM_S    = 0;
constexpr int SM_X    = 20 * UNIT;
constexpr int SM_T    = 23 * UNIT;
constexpr int SM_MISC = SM_T + 4 * KB;
constexpr int SM_END  = SM_MISC + 2464;
constexpr int SLICE_END = 128 + N * 16;
constexpr int X_OUT  = SM_X + UNIT;
constexpr int X_TAB  = X_OUT;
constexpr int X_RU   = X_TAB + NPC * 64 + 16;
constexpr int X_DEF  = X_RU + NPC * 4;
constexpr int X_ZERO = X_OUT + UNIT - 2048;
constexpr int X_IMG  = X_OUT + UNIT;
constexpr int X_CNT  = X_IMG + NPC * 64;
static_assert(X_DEF + 640 <= X_ZERO && X_CNT + NPC * 32 + 128 <= SM_T, "list scratch");
constexpr int B_K = 0, B_QK = 32, B_EPO = 40,
              B_A = 48,
              B_F = 176, B_HS = 272, B_Q = 280, B_R = 288,
              B_GO = 296, B_LF = 304, B_TF = 312, B_RGO = 320, B_CGO = 328, B_MI = 336, B_HR = 344,
              B_Z = 352,
              B_FA = 360, B_XF = 392, B_SENT = 400, B_S = 408, B_VE = 416,
              B_RND = 424;
constexpr int B_HV = 528, B_RV = 536;
constexpr int MI_EPOCH = 544, MI_EBAD = 548, MI_SLOW = 552, MI_NOVF = 556, MI_FLAGS = 560, MI_TOUCH = 564;
constexpr int MI_OVF  = 1280;
constexpr int MI_ES   = 768;
constexpr int MI_PCNT = 1792;
constexpr int MI_DIS  = 2304;
constexpr int A0 = 0, A1 = 4, A2 = 8, A3 = 12, A4 = 16, A5 = 19;
constexpr uint32_t A_TILES = A3 | A1 << 8 | A2 << 16 | A0 << 24;
#define PROMO CU_TENSOR_MAP_L2_PROMOTION_L2_128B
#define EFETCH 1
#define VPF 1
#define RPER 0
#define ER 2
#define G3 1
#define XORD 0x04156273
#define LGATE 1
#define AUNRV 1
constexpr int AUNR = AUNRV;
#define WPROF 0
#define MW 2
#define SROT 1
#define OB 6
#define HGATE 0
#define CHK1 1
#define HPER 160
#define HRW 1
#define T0BAR B_CGO

constexpr uint32_t W_OVF = 1u << 24, W_EBAD = 1u << 25;
constexpr int CELLN = 20;

__device__ uint4         g_cells[RCTA * NCTA * 4];
__device__ uint4         g_H[32 * N];
__device__ uint4         g_idx[NSET * 32];
__device__ __nv_bfloat16 g_M[D * D];
__device__ uint32_t      g_sync[24 * 32];
constexpr int SY_M = 16 * 32, SY_H = 17 * 32, SY_L = 18 * 32, SY_R = 19 * 32, SY_SLOW = 20 * 32;
#define PROF(i) do {} while (0)
#define PROF_FLUSH() do {} while (0)
constexpr int SM_ALLOC = SM_END;
static_assert(SM_ALLOC <= 232448, "shared memory");

struct Params {
    const int* src; const int* dst;
    uint32_t* sync;
    const int* esrc; const int* edst4;
    int Efast, chunk;
    const __nv_bfloat16* dis;
    const char* x; const char* wv;
    uint4* cells; uint2* M;
    uint4* idx; uint4* H; uint4* out;
    const int* edst;
    int E, Ee;
};

__device__ __forceinline__ uint32_t s32(const void* p) { return (uint32_t)__cvta_generic_to_shared(p); }
__device__ __forceinline__ void mbar_init(uint32_t a, uint32_t cnt) { asm volatile("mbarrier.init.shared.b64 [%0], %1;" :: "r"(a), "r"(cnt) : "memory"); }
__device__ __forceinline__ void mbar_arrive(uint32_t a) { asm volatile("mbarrier.arrive.shared.b64 _, [%0];" :: "r"(a) : "memory"); }
__device__ __forceinline__ void mbar_expect(uint32_t a, uint32_t bytes) { asm volatile("mbarrier.arrive.expect_tx.shared.b64 _, [%0], %1;" :: "r"(a), "r"(bytes) : "memory"); }
__device__ __forceinline__ void mbar_wait(uint32_t a, uint32_t parity) {
    uint32_t ok = 0;
#pragma unroll 1
    for (int it = 0; it < SPIN_LIMIT && !ok; ++it)
        asm volatile("{\n.reg .pred p;\nmbarrier.try_wait.parity.shared.b64 p, [%1], %2;\nselp.u32 %0, 1, 0, p;\n}"
                     : "=r"(ok) : "r"(a), "r"(parity) : "memory");
}
__device__ __forceinline__ bool elect() { uint32_t r; asm volatile("{\n.reg .pred p;\nelect.sync _|p, 0xffffffff;\nselp.u32 %0, 1, 0, p;\n}" : "=r"(r) :: "memory"); return r; }
__device__ __forceinline__ void warp_arrive(uint32_t a) {
    asm volatile("{\n.reg .pred p;\nelect.sync _|p, 0xffffffff;\n@p mbarrier.arrive.shared.b64 _, [%0];\n}" :: "r"(a) : "memory");
}
__device__ __forceinline__ void bar_sync(int id, int n)   { __syncwarp(); asm volatile("bar.sync %0, %1;"   :: "r"(id), "r"(n) : "memory"); }
__device__ __forceinline__ void bar_arrive(int id, int n) { __syncwarp(); asm volatile("bar.arrive %0, %1;" :: "r"(id), "r"(n) : "memory"); }
__device__ __forceinline__ void fence_async_smem() { asm volatile("fence.proxy.async.shared::cta;" ::: "memory"); }
__device__ __forceinline__ void fence_async_gmem() { asm volatile("fence.proxy.async.global;" ::: "memory"); }
__device__ __forceinline__ void tma2d(uint32_t dst, const CUtensorMap* tm, int c0, int c1, uint32_t bar) {
    asm volatile("cp.async.bulk.tensor.2d.shared::cluster.global.mbarrier::complete_tx::bytes [%0], [%1, {%3, %4}], [%2];"
                 :: "r"(dst), "l"(tm), "r"(bar), "r"(c0), "r"(c1) : "memory");
}
__device__ __forceinline__ void tma3d(uint32_t dst, const CUtensorMap* tm, int row, uint32_t bar) {
    asm volatile("cp.async.bulk.tensor.3d.shared::cluster.global.mbarrier::complete_tx::bytes [%0], [%1, {%4, %3, %4}], [%2];"
                 :: "r"(dst), "l"(tm), "r"(bar), "r"(row), "r"(0) : "memory");
}
__device__ __forceinline__ void tma2d_store(const CUtensorMap* tm, uint32_t src, int c0, int c1) {
    asm volatile("cp.async.bulk.tensor.2d.global.shared::cta.bulk_group [%0, {%2, %3}], [%1];"
                 :: "l"(tm), "r"(src), "r"(c0), "r"(c1) : "memory");
}
__device__ __forceinline__ void tma2d_add(const CUtensorMap* tm, uint32_t src, int c0, int c1) {
    asm volatile("cp.reduce.async.bulk.tensor.2d.global.shared::cta.add.bulk_group [%0, {%2, %3}], [%1];"
                 :: "l"(tm), "r"(src), "r"(c0), "r"(c1) : "memory");
}
__device__ __forceinline__ void bulk_load(uint32_t dst, const void* src, uint32_t bytes, uint32_t bar) {
    asm volatile("cp.async.bulk.shared::cluster.global.mbarrier::complete_tx::bytes [%0], [%1], %2, [%3];"
                 :: "r"(dst), "l"(src), "r"(bytes), "r"(bar) : "memory");
}
__device__ __forceinline__ void bulk_store(void* dst, uint32_t src, uint32_t bytes) {
    asm volatile("cp.async.bulk.global.shared::cta.bulk_group [%0], [%1], %2;" :: "l"(dst), "r"(src), "r"(bytes) : "memory");
}
__device__ __forceinline__ uint32_t clk() { uint32_t c; asm volatile("mov.u32 %0, %%clock;" : "=r"(c) :: "memory"); return c; }
__device__ __forceinline__ void wait_clk(uint32_t t) { while ((int)(clk() - t) < 0) {} }
__device__ __forceinline__ void bulk_commit() { asm volatile("cp.async.bulk.commit_group;" ::: "memory"); }
template <int K> __device__ __forceinline__ void bulk_wait_read() { asm volatile("cp.async.bulk.wait_group.read %0;" :: "n"(K) : "memory"); }
__device__ __forceinline__ void prefetch_map(const CUtensorMap* tm) { asm volatile("prefetch.tensormap [%0];" :: "l"(tm) : "memory"); }
__device__ __forceinline__ uint4 lds128(uint32_t a) { uint4 v; asm volatile("ld.shared.v4.u32 {%0,%1,%2,%3}, [%4];" : "=r"(v.x), "=r"(v.y), "=r"(v.z), "=r"(v.w) : "r"(a) : "memory"); return v; }
__device__ __forceinline__ void sts128(uint32_t a, uint4 v) { asm volatile("st.shared.v4.u32 [%0], {%1,%2,%3,%4};" :: "r"(a), "r"(v.x), "r"(v.y), "r"(v.z), "r"(v.w) : "memory"); }
__device__ __forceinline__ uint32_t lds32(uint32_t a) { uint32_t v; asm volatile("ld.shared.u32 %0, [%1];" : "=r"(v) : "r"(a) : "memory"); return v; }
__device__ __forceinline__ void sts32(uint32_t a, uint32_t v) { asm volatile("st.shared.u32 [%0], %1;" :: "r"(a), "r"(v) : "memory"); }
__device__ __forceinline__ void sts16(uint32_t a, uint32_t v) { asm volatile("st.shared.u16 [%0], %1;" :: "r"(a), "h"((unsigned short)v) : "memory"); }
__device__ __forceinline__ uint32_t atoms_add(uint32_t a, uint32_t x) { uint32_t v; asm volatile("atom.shared.add.u32 %0, [%1], %2;" : "=r"(v) : "r"(a), "r"(x) : "memory"); return v; }
__device__ __forceinline__ uint32_t ld_relaxed(const uint32_t* p) { uint32_t v; asm volatile("ld.relaxed.gpu.global.u32 %0, [%1];" : "=r"(v) : "l"(p) : "memory"); return v; }
__device__ __forceinline__ uint4 ld_relaxed4(const uint4* p) { uint4 v; asm volatile("ld.relaxed.gpu.global.L1::no_allocate.v4.u32 {%0,%1,%2,%3}, [%4];" : "=r"(v.x), "=r"(v.y), "=r"(v.z), "=r"(v.w) : "l"(p) : "memory"); return v; }
__device__ __forceinline__ uint32_t ld_acquire(const uint32_t* p) { uint32_t v; asm volatile("ld.acquire.gpu.global.u32 %0, [%1];" : "=r"(v) : "l"(p) : "memory"); return v; }
__device__ __forceinline__ void st_relaxed(uint32_t* p, uint32_t v) { asm volatile("st.relaxed.gpu.global.u32 [%0], %1;" :: "l"(p), "r"(v) : "memory"); }
__device__ __forceinline__ void red_relaxed(uint32_t* p) { asm volatile("red.relaxed.gpu.global.add.u32 [%0], 1;" :: "l"(p) : "memory"); }
__device__ __forceinline__ uint32_t list_tag(uint32_t epoch) { return (epoch % 3u + 1u) * 0x40004000u; }
__device__ __forceinline__ void red_release(uint32_t* p) { asm volatile("red.release.gpu.global.add.u32 [%0], 1;" :: "l"(p) : "memory"); }
__device__ __forceinline__ void wait_count(const uint32_t* p, uint32_t target) {
#pragma unroll 1
    for (int it = 0; it < SPIN_LIMIT; ++it)
        if ((int)(ld_acquire(p) - target) >= 0) break;
}
__device__ __forceinline__ bool mbar_test(uint32_t a, uint32_t parity) {
    uint32_t ok;
    asm volatile("{\n.reg .pred p;\nmbarrier.test_wait.parity.shared.b64 p, [%1], %2;\nselp.u32 %0, 1, 0, p;\n}" : "=r"(ok) : "r"(a), "r"(parity) : "memory");
    return __all_sync(0xffffffffu, ok);
}
__device__ __forceinline__ uint4 ldg_in(const void* p) { uint4 v; asm volatile("ld.global.nc.L1::no_allocate.v4.u32 {%0,%1,%2,%3}, [%4];" : "=r"(v.x), "=r"(v.y), "=r"(v.z), "=r"(v.w) : "l"(p)); return v; }
__device__ __forceinline__ uint4 ldg_sc(const void* p) { uint4 v; asm volatile("ld.global.L1::no_allocate.v4.u32 {%0,%1,%2,%3}, [%4];" : "=r"(v.x), "=r"(v.y), "=r"(v.z), "=r"(v.w) : "l"(p) : "memory"); return v; }
__device__ __forceinline__ void red_row(uint4* p, uint4 v) { asm volatile("red.relaxed.gpu.global.add.noftz.v4.bf16x2 [%0], {%1,%2,%3,%4};" :: "l"(p), "r"(v.x), "r"(v.y), "r"(v.z), "r"(v.w) : "memory"); }
__device__ __forceinline__ uint32_t pack_bf16(float lo, float hi) { uint32_t r; asm("cvt.rn.bf16x2.f32 %0, %1, %2;" : "=r"(r) : "f"(hi), "f"(lo)); return r; }
__device__ __forceinline__ float blo(uint32_t v) { return __uint_as_float(v << 16); }
__device__ __forceinline__ float bhi(uint32_t v) { return __uint_as_float(v & 0xffff0000u); }
__device__ __forceinline__ const char* row_ptr(const char* base, uint32_t row) {
    uint64_t r; asm("mad.wide.u32 %0, %1, 512, %2;" : "=l"(r) : "r"(row), "l"((uint64_t)base)); return (const char*)r;
}

constexpr uint32_t DESC_HI = 64u | (1u << 30);
__device__ __forceinline__ uint32_t desc_lo(uint32_t addr) { return ((addr & 0x3FFFF) >> 4) | (1u << 16); }
__device__ __forceinline__ void wg_fence()  { asm volatile("wgmma.fence.sync.aligned;" ::: "memory"); }
__device__ __forceinline__ void wg_commit() { asm volatile("wgmma.commit_group.sync.aligned;" ::: "memory"); }
template <int K> __device__ __forceinline__ void wg_wait() { asm volatile("wgmma.wait_group.sync.aligned %0;" :: "n"(K) : "memory"); }
#define GK_ACC(c) c(d[0]), c(d[1]), c(d[2]), c(d[3]), c(d[4]), c(d[5]), c(d[6]), c(d[7]), c(d[8]), c(d[9]), \
    c(d[10]), c(d[11]), c(d[12]), c(d[13]), c(d[14]), c(d[15]), c(d[16]), c(d[17]), c(d[18]), c(d[19]), \
    c(d[20]), c(d[21]), c(d[22]), c(d[23]), c(d[24]), c(d[25]), c(d[26]), c(d[27]), c(d[28]), c(d[29]), \
    c(d[30]), c(d[31]), c(d[32]), c(d[33]), c(d[34]), c(d[35]), c(d[36]), c(d[37]), c(d[38]), c(d[39])
#define GK_WGMMA(P) "{\n.reg .pred p;\n.reg .b64 da, db;\nsetp.ne.b32 p, " P ", 0;\nmov.b64 da, {%40, %42};\nmov.b64 db, {%41, %42};\n" \
    "wgmma.mma_async.sync.aligned.m64n80k16.f32.bf16.bf16 " \
    "{%0,%1,%2,%3,%4,%5,%6,%7,%8,%9,%10,%11,%12,%13,%14,%15,%16,%17,%18,%19," \
    "%20,%21,%22,%23,%24,%25,%26,%27,%28,%29,%30,%31,%32,%33,%34,%35,%36,%37,%38,%39}, da, db, p, 1, 1, 1, 0;\n}\n"
template <bool FIRST>
__device__ __forceinline__ void wgmma80(float (&d)[40], uint32_t alo, uint32_t blo_) {
    if (FIRST) asm volatile(GK_WGMMA("0") : GK_ACC("=f") : "r"(alo), "r"(blo_), "r"(DESC_HI));
    else       asm volatile(GK_WGMMA("1") : GK_ACC("+f") : "r"(alo), "r"(blo_), "r"(DESC_HI));
}
template <int KQ>
__device__ __forceinline__ void gemm_quarter(float (&d)[40], uint32_t unit, uint32_t tile, uint32_t bar, uint32_t parity, uint32_t rel = 0) {
    mbar_wait(bar + KQ * 8, parity);
    __syncwarp();
    const uint32_t a = desc_lo(unit), b = desc_lo(tile) + ((KQ * KB) >> 4);
    wg_fence();
    wgmma80<KQ == 0>(d, a, b);
    if (KQ) { wg_commit(); wg_wait<1>(); warp_arrive(rel); }
    wgmma80<false>(d, a + 128, b + 2);
    wgmma80<false>(d, a + 256, b + 4);
    wgmma80<false>(d, a + 384, b + 6);
    wg_commit();
}
__device__ __forceinline__ void stsm4t(uint32_t a, uint32_t r0, uint32_t r1, uint32_t r2, uint32_t r3) {
    asm volatile("stmatrix.sync.aligned.m8n8.x4.trans.shared.b16 [%0], {%1,%2,%3,%4};" :: "r"(a), "r"(r0), "r"(r1), "r"(r2), "r"(r3) : "memory");
}
__device__ __forceinline__ void stsm4(uint32_t a, uint32_t r0, uint32_t r1, uint32_t r2, uint32_t r3) {
    asm volatile("stmatrix.sync.aligned.m8n8.x4.shared.b16 [%0], {%1,%2,%3,%4};" :: "r"(a), "r"(r0), "r"(r1), "r"(r2), "r"(r3) : "memory");
}
__device__ __forceinline__ uint4 ldsm4(uint32_t a) {
    uint4 v; asm volatile("ldmatrix.sync.aligned.m8n8.x4.shared.b16 {%0,%1,%2,%3}, [%4];" : "=r"(v.x), "=r"(v.y), "=r"(v.z), "=r"(v.w) : "r"(a) : "memory"); return v;
}
__device__ __forceinline__ void mma16816(float (&c)[4], uint32_t a0, uint32_t a1, uint32_t a2, uint32_t a3, uint32_t b0, uint32_t b1) {
    asm volatile("mma.sync.aligned.m16n8k16.row.col.f32.bf16.bf16.f32 {%0,%1,%2,%3}, {%4,%5,%6,%7}, {%8,%9}, {%0,%1,%2,%3};"
        : "+f"(c[0]), "+f"(c[1]), "+f"(c[2]), "+f"(c[3]) : "r"(a0), "r"(a1), "r"(a2), "r"(a3), "r"(b0), "r"(b1));
}
__device__ __forceinline__ void pack_acc(uint32_t (&h)[20], const float (&d)[40]) {
#pragma unroll
    for (int i = 0; i < 20; ++i) h[i] = pack_bf16(d[2 * i], d[2 * i + 1]);
}
__device__ __forceinline__ void store_tile(const uint32_t (&h)[20], uint32_t tile, int mt, int w4, int lane) {
    const int r = lane & 7;
    const uint32_t base = tile + mt * KB + (((lane >> 4) * 8 + r) * 128) + (((2 * w4 + ((lane >> 3) & 1)) ^ r) << 4);
#pragma unroll
    for (int i = 0; i < 5; ++i) stsm4t(base + i * 2048, h[4 * i], h[4 * i + 1], h[4 * i + 2], h[4 * i + 3]);
}
__device__ __forceinline__ void fma8(float (&a)[8], float w, const uint4& v) {
    a[0] = fmaf(w, blo(v.x), a[0]); a[1] = fmaf(w, bhi(v.x), a[1]);
    a[2] = fmaf(w, blo(v.y), a[2]); a[3] = fmaf(w, bhi(v.y), a[3]);
    a[4] = fmaf(w, blo(v.z), a[4]); a[5] = fmaf(w, bhi(v.z), a[5]);
    a[6] = fmaf(w, blo(v.w), a[6]); a[7] = fmaf(w, bhi(v.w), a[7]);
}
__device__ __forceinline__ float dot8(const float (&q)[8], const uint4& v) {
    float s = q[0] * blo(v.x);
    s = fmaf(q[1], bhi(v.x), s); s = fmaf(q[2], blo(v.y), s); s = fmaf(q[3], bhi(v.y), s);
    s = fmaf(q[4], blo(v.z), s); s = fmaf(q[5], bhi(v.z), s); s = fmaf(q[6], blo(v.w), s); s = fmaf(q[7], bhi(v.w), s);
    return s;
}
__device__ __forceinline__ uint4 pack8(const float (&a)[8], float s) {
    return make_uint4(pack_bf16(a[0] * s, a[1] * s), pack_bf16(a[2] * s, a[3] * s), pack_bf16(a[4] * s, a[5] * s), pack_bf16(a[6] * s, a[7] * s));
}
__device__ __forceinline__ uint32_t hmul2(uint32_t a, uint32_t b) { uint32_t d; asm("mul.rn.bf16x2 %0, %1, %2;" : "=r"(d) : "r"(a), "r"(b)); return d; }
__device__ __forceinline__ uint32_t tile_chunk(uint32_t tile, int r, int c) {
    return tile + (c >> 3) * KB + r * 128 + (((c & 7) ^ (r & 7)) << 4);
}
__device__ __forceinline__ uint32_t wsum4(const uint32_t (&a)[4], uint32_t r0, uint32_t r1, uint32_t r2, uint32_t r3) {
    uint32_t z;
    asm("{\n.reg .b32 t;\nmul.rn.bf16x2 t, %1, %5;\nfma.rn.bf16x2 t, %2, %6, t;\nfma.rn.bf16x2 t, %3, %7, t;\nfma.rn.bf16x2 %0, %4, %8, t;\n}"
        : "=r"(z) : "r"(a[0]), "r"(a[1]), "r"(a[2]), "r"(a[3]), "r"(r0), "r"(r1), "r"(r2), "r"(r3));
    return z;
}
__device__ __forceinline__ void softmax4(const float (&s)[4], const float (&u)[4], int lane, uint32_t (&a)[4]) {
    const bool b = lane & 4, c = lane & 8;
    const float k0 = (b ? u[1] : s[0]) + __shfl_xor_sync(0xffffffffu, b ? s[1] : u[0], 4);
    const float k1 = (b ? u[3] : s[2]) + __shfl_xor_sync(0xffffffffu, b ? s[3] : u[2], 4);
    const float e = (c ? k1 : k0) + __shfl_xor_sync(0xffffffffu, c ? k0 : k1, 9);
    float pe;
    asm("ex2.approx.ftz.f32 %0, %1;" : "=f"(pe) : "f"(e * (0.0625f * 1.4426950408889634f)));
    const int l0 = (lane >> 4) * 18;
    const float p0 = __shfl_sync(0xffffffffu, pe, l0), p1 = __shfl_sync(0xffffffffu, pe, l0 + 9);
    const float p2 = __shfl_sync(0xffffffffu, pe, l0 + 4), p3 = __shfl_sync(0xffffffffu, pe, l0 + 13);
    float inv;
    asm("rcp.approx.ftz.f32 %0, %1;" : "=f"(inv) : "f"(((p0 + p1) + (p2 + p3)) + 1e-9f));
    a[0] = pack_bf16(p0 * inv, p0 * inv); a[1] = pack_bf16(p1 * inv, p1 * inv);
    a[2] = pack_bf16(p2 * inv, p2 * inv); a[3] = pack_bf16(p3 * inv, p3 * inv);
}
__device__ __forceinline__ void attention_chunks(const uint4 (&r)[4][2], uint32_t tile, int node, int lane) {
    const uint32_t qa = tile_chunk(tile, node + (lane >> 4), lane & 15);
    const uint4 q0 = lds128(qa), q1 = lds128(qa + 2 * KB);
    float s[4] = {0.f, 0.f, 0.f, 0.f}, u[4] = {0.f, 0.f, 0.f, 0.f};
    mma16816(s, r[0][0].x, r[1][0].x, r[0][0].y, r[1][0].y, q0.x, q0.y); mma16816(u, r[2][0].x, r[3][0].x, r[2][0].y, r[3][0].y, q0.x, q0.y);
    mma16816(s, r[0][0].z, r[1][0].z, r[0][0].w, r[1][0].w, q0.z, q0.w); mma16816(u, r[2][0].z, r[3][0].z, r[2][0].w, r[3][0].w, q0.z, q0.w);
    mma16816(s, r[0][1].x, r[1][1].x, r[0][1].y, r[1][1].y, q1.x, q1.y); mma16816(u, r[2][1].x, r[3][1].x, r[2][1].y, r[3][1].y, q1.x, q1.y);
    mma16816(s, r[0][1].z, r[1][1].z, r[0][1].w, r[1][1].w, q1.z, q1.w); mma16816(u, r[2][1].z, r[3][1].z, r[2][1].w, r[3][1].w, q1.z, q1.w);
    uint32_t a[4];
    softmax4(s, u, lane, a);
#pragma unroll
    for (int h = 0; h < 2; ++h)
        sts128(qa + h * 2 * KB, make_uint4(wsum4(a, r[0][h].x, r[1][h].x, r[2][h].x, r[3][h].x), wsum4(a, r[0][h].y, r[1][h].y, r[2][h].y, r[3][h].y),
                                           wsum4(a, r[0][h].z, r[1][h].z, r[2][h].z, r[3][h].z), wsum4(a, r[0][h].w, r[1][h].w, r[2][h].w, r[3][h].w)));
}
__device__ __forceinline__ void attention_frags(const uint4 (&r)[2][4], uint32_t tile, int node, int lane) {
    const int nd = node + ((lane >> 2) & 1);
    const uint32_t qa = tile + (lane >> 4) * KB + nd * 128 + (((lane ^ (lane >> 1 & 4) ^ nd) & 7) << 4);
    const uint4 q0 = ldsm4(qa), q1 = ldsm4(qa + 2 * KB);
    float s[4] = {0.f, 0.f, 0.f, 0.f}, u[4] = {0.f, 0.f, 0.f, 0.f};
    mma16816(s, r[0][0].x, r[0][0].y, r[0][0].z, r[0][0].w, q0.x, q0.y); mma16816(u, r[1][0].x, r[1][0].y, r[1][0].z, r[1][0].w, q0.x, q0.y);
    mma16816(s, r[0][1].x, r[0][1].y, r[0][1].z, r[0][1].w, q0.z, q0.w); mma16816(u, r[1][1].x, r[1][1].y, r[1][1].z, r[1][1].w, q0.z, q0.w);
    mma16816(s, r[0][2].x, r[0][2].y, r[0][2].z, r[0][2].w, q1.x, q1.y); mma16816(u, r[1][2].x, r[1][2].y, r[1][2].z, r[1][2].w, q1.x, q1.y);
    mma16816(s, r[0][3].x, r[0][3].y, r[0][3].z, r[0][3].w, q1.z, q1.w); mma16816(u, r[1][3].x, r[1][3].y, r[1][3].z, r[1][3].w, q1.z, q1.w);
    uint32_t a[4];
    softmax4(s, u, lane, a);
#pragma unroll
    for (int h = 0; h < 2; ++h)
        stsm4(qa + h * 2 * KB, wsum4(a, r[0][2 * h].x, r[0][2 * h].y, r[1][2 * h].x, r[1][2 * h].y), wsum4(a, r[0][2 * h].z, r[0][2 * h].w, r[1][2 * h].z, r[1][2 * h].w),
              wsum4(a, r[0][2 * h + 1].x, r[0][2 * h + 1].y, r[1][2 * h + 1].x, r[1][2 * h + 1].y), wsum4(a, r[0][2 * h + 1].z, r[0][2 * h + 1].w, r[1][2 * h + 1].z, r[1][2 * h + 1].w));
}
__device__ __noinline__ void attention_generic(const Params& p, uint32_t tile, int nl, int node, int lane) {
    const uint32_t qa = tile_chunk(tile, nl, lane);
    const uint4 qv = lds128(qa);
    const float q[8] = {blo(qv.x), bhi(qv.x), blo(qv.y), bhi(qv.y), blo(qv.z), bhi(qv.z), blo(qv.w), bhi(qv.w)};
    float z[8] = {0.f, 0.f, 0.f, 0.f, 0.f, 0.f, 0.f, 0.f};
    float den = 0.f;
#pragma unroll 1
    for (int e = 0; e < p.Ee; e += 32) {
        const bool m = (e + lane < p.Ee) && (__ldg(p.edst + e + lane) == node);
        const int sv = m ? __ldg(p.esrc + e + lane) : 0;
        uint32_t bal = __ballot_sync(0xffffffffu, m);
        while (bal) {
            const int l = __ffs(bal) - 1; bal &= bal - 1;
            const uint4 v = ldg_in(row_ptr(p.x + lane * 16, __shfl_sync(0xffffffffu, sv, l)));
            float c = dot8(q, v);
#pragma unroll
            for (int o = 16; o; o >>= 1) c += __shfl_xor_sync(0xffffffffu, c, o);
            const float pe = expf(c * 0.0625f);
            den += pe;
            fma8(z, pe, v);
        }
    }
    sts128(qa, pack8(z, 1.f / (den + 1e-9f)));
}
__device__ __noinline__ void local_generic(const Params& p, int node0, int w, int lane) {
    float a0[8], a1[8], a2[8], a3[8];
#pragma unroll
    for (int k = 0; k < 8; ++k) { a0[k] = 0.f; a1[k] = 0.f; a2[k] = 0.f; a3[k] = 0.f; }
#pragma unroll 1
    for (int e = 0; e < p.E; e += 32) {
        const int dl = (e + lane < p.E) ? __ldg(p.dst + e + lane) - node0 - w : -1;
        const int k = dl == 0 ? 0 : dl == AW ? 1 : dl == 2 * AW ? 2 : (dl == 3 * AW && w + 3 * AW < NPC) ? 3 : -1;
        const int sv = k >= 0 ? __ldg(p.src + e + lane) : 0;
        uint32_t bal = __ballot_sync(0xffffffffu, k >= 0);
        while (bal) {
            const int l = __ffs(bal) - 1; bal &= bal - 1;
            const int s = __shfl_sync(0xffffffffu, sv, l), kk = __shfl_sync(0xffffffffu, k, l);
            const uint4 v = ldg_sc(p.H + lane * N + s);
            if (kk & 2) { if (kk & 1) fma8(a3, 1.f, v); else fma8(a2, 1.f, v); }
            else        { if (kk & 1) fma8(a1, 1.f, v); else fma8(a0, 1.f, v); }
        }
    }
    const int n = node0 + w;
    red_row(p.out + n * 32 + lane, pack8(a0, __bfloat162float(p.dis[n])));
    red_row(p.out + (n + AW) * 32 + lane, pack8(a1, __bfloat162float(p.dis[n + AW])));
    red_row(p.out + (n + 2 * AW) * 32 + lane, pack8(a2, __bfloat162float(p.dis[n + 2 * AW])));
    if (w + 3 * AW < NPC) red_row(p.out + (n + 3 * AW) * 32 + lane, pack8(a3, __bfloat162float(p.dis[n + 3 * AW])));
}
__device__ __forceinline__ uint32_t hadd2(uint32_t a, uint32_t b) { uint32_t d; asm("add.rn.bf16x2 %0, %1, %2;" : "=r"(d) : "r"(a), "r"(b)); return d; }
__device__ __forceinline__ float plo(uint32_t v) { uint32_t d; asm("prmt.b32 %0, %1, 0, 0x1044;" : "=r"(d) : "r"(v)); return __uint_as_float(d); }
template <int HI, int NR>
__device__ __forceinline__ uint32_t agg_sum(uint32_t w, uint32_t base) {
    uint32_t a, r0, r1, r2, r3;
    if (HI) asm("dp2a.hi.u32.u32 %0, %1, %2, %3;" : "=r"(a) : "r"(w), "r"(0x10000010u), "r"(base));
    else    asm("dp2a.lo.u32.u32 %0, %1, %2, %3;" : "=r"(a) : "r"(w), "r"(0x10000010u), "r"(base));
    if (NR == 2) {
        asm volatile("ldmatrix.sync.aligned.m8n8.x2.shared.b16 {%0,%1}, [%2];" : "=r"(r0), "=r"(r1) : "r"(a));
        return hadd2(r0, r1);
    }
    asm volatile("ldmatrix.sync.aligned.m8n8.x4.shared.b16 {%0,%1,%2,%3}, [%4];" : "=r"(r0), "=r"(r1), "=r"(r2), "=r"(r3) : "r"(a));
    return hadd2(hadd2(r0, r1), hadd2(r2, r3));
}
struct Unit { uint4 a, b; };
__device__ __forceinline__ uint32_t unit_stale(const Unit& x, uint32_t lt) {
    if (CHK1) return ((x.a.x ^ lt) | (x.b.x ^ lt)) & 0xc000u;
    const uint32_t o = x.a.x | x.a.y | x.a.z | x.a.w | x.b.x | x.b.y | x.b.z | x.b.w, a = x.a.x & x.a.y & x.a.z & x.a.w & x.b.x & x.b.y & x.b.z & x.b.w;
    return ((o ^ lt) | (a ^ lt)) & 0xc000u;
}
__device__ __forceinline__ uint32_t agg_tail(float lo, float hi, uint32_t s, const uint4& w, uint32_t base, uint32_t b5, uint32_t b6) {
    if (b5 > 0xffffu) {
        s = hadd2(s, agg_sum<1, 4>(w.z, base));
        if (b6) {
            const uint32_t u = b6 > 0xffffu ? agg_sum<0, 4>(w.w, base) : agg_sum<0, 2>(w.w, base);
            lo += plo(u); hi += bhi(u);
        }
    } else if (b5) s = hadd2(s, agg_sum<1, 2>(w.z, base));
    const float f = bhi(w.w);
    return pack_bf16((lo + plo(s)) * f, (hi + bhi(s)) * f);
}
__device__ __forceinline__ void agg_unit(const Unit& x, uint32_t base, uint32_t stg, uint32_t lt) {
    const uint32_t s0 = hadd2(agg_sum<0, 4>(x.a.x, base), agg_sum<1, 4>(x.a.x, base)), u0 = hadd2(agg_sum<0, 4>(x.b.x, base), agg_sum<1, 4>(x.b.x, base));
    const uint32_t s1 = hadd2(agg_sum<0, 4>(x.a.y, base), agg_sum<1, 4>(x.a.y, base)), u1 = hadd2(agg_sum<0, 4>(x.b.y, base), agg_sum<1, 4>(x.b.y, base));
    const uint32_t s2 = agg_sum<0, 4>(x.a.z, base), u2 = agg_sum<0, 4>(x.b.z, base);
    const uint32_t a5 = __ballot_sync(0xffffffffu, x.a.z > (lt | 0xffffu)), a6 = __ballot_sync(0xffffffffu, x.a.w & 0x3fffu);
    const uint32_t b5 = __ballot_sync(0xffffffffu, x.b.z > (lt | 0xffffu)), b6 = __ballot_sync(0xffffffffu, x.b.w & 0x3fffu);
    const uint32_t oa = agg_tail(plo(s0) + plo(s1), bhi(s0) + bhi(s1), s2, x.a, base, a5, a6);
    const uint32_t ob = agg_tail(plo(u0) + plo(u1), bhi(u0) + bhi(u1), u2, x.b, base, b5, b6);
    asm volatile("stmatrix.sync.aligned.m8n8.x2.shared.b16 [%0], {%1,%2};" :: "r"(stg), "r"(oa), "r"(ob) : "memory");
}

__global__ void __launch_bounds__(NTHR, 1)
fused_kernel(const __grid_constant__ Params p,
             const __grid_constant__ CUtensorMap tmX, const __grid_constant__ CUtensorMap tmWl,
             const __grid_constant__ CUtensorMap tmM, const __grid_constant__ CUtensorMap tmWv,
             const __grid_constant__ CUtensorMap tmR, const __grid_constant__ CUtensorMap tmO,
             const __grid_constant__ CUtensorMap tmG, const __grid_constant__ CUtensorMap tmQ,
             const __grid_constant__ CUtensorMap tmK, const __grid_constant__ CUtensorMap tmV3)
{
    extern __shared__ __align__(1024) unsigned char smem[];
    const uint32_t sb = s32(smem);
    const int tid = threadIdx.x, lane = tid & 31;
    const int warp = __shfl_sync(0xffffffffu, tid >> 5, 0);
    const int cta = blockIdx.x;
    const int node0 = cta * NPC;
    const bool rowcta = cta < RCTA;
    const int slice = cta >> 2, quarter = cta & 3;
    const int nlast = 12 + (quarter == 3);
    const int i0 = (cta >> 3) * 16, j0 = (cta & 7) * 32;
    const uint32_t bars = sb + SM_MISC;
    const uint32_t sS = sb + SM_S, sT = sb + SM_T;

    const bool stage = rowcta && p.edst4;
    auto slow_cta = [&]() { uint32_t a, b; asm volatile("ld.shared.v2.u32 {%0, %1}, [%2];" : "=r"(a), "=r"(b) : "r"(bars + MI_SLOW) : "memory"); return a || b > OVCAP; };
    auto publish = [&](int set) {
        const uint4 dv = lds128(bars + MI_DIS + set * 16);
        uint4 v = lds128(sb + X_IMG + set * 512 + lane * 16);
        const uint4 z = lds128(sb + X_DEF + set * 64 + (lane & 3) * 16);
        if ((lane & 3) == 3) { v.x = __byte_perm(v.x, v.y, 0x5410); v.y = v.w; }
        v.x = __vmaxu2(v.x, z.x); v.y = __vmaxu2(v.y, z.y); v.z = __vmaxu2(v.z, z.z); v.w = __vmaxu2(v.w, z.w);
        if (slow_cta()) v = make_uint4(0, 0, 0, 0);
        const uint32_t lt = list_tag(lds32(bars + MI_EPOCH));
        v.x |= lt; v.y |= lt; v.z |= lt; v.w |= lt;
        if ((lane & 3) == 3) { const uint32_t sel = lane & 16 ? 0x7632 : 0x5410; v.z = __byte_perm(dv.x, dv.y, sel); v.w = __byte_perm(dv.z, dv.w, sel); }
        uint32_t* ip = (uint32_t*)p.idx + (cta * 10 + set) * 128 + lane;
        st_relaxed(ip, __byte_perm(v.x, v.z, 0x5410));      st_relaxed(ip + 32, __byte_perm(v.x, v.z, 0x7632));
        st_relaxed(ip + 64, __byte_perm(v.y, v.w, 0x5410)); st_relaxed(ip + 96, __byte_perm(v.y, v.w, 0x7632));
    };

    if (warp >= AW) {
        const int pw = warp - AW;
        auto init = [&](int b0, int b1, int c) {
#pragma unroll
            for (int b = b0; b < b1; b += 8) mbar_init(bars + b, c);
        };
        uint4 pe = make_uint4(0, 0, 0, 0);
        if (pw == 0) {
            if (elect()) {
                PROF(0);
                prefetch_map(&tmQ); prefetch_map(&tmK); prefetch_map(&tmX); prefetch_map(&tmWl);
                init(B_K, B_A, 1);
                asm volatile("fence.mbarrier_init.release.cluster;" ::: "memory");
                mbar_expect(bars + B_QK, 3 * UNIT);
                tma3d(sS + A3 * UNIT, &tmQ, i0, bars + B_QK);
                tma3d(sS + (A3 + 1) * UNIT, &tmK, j0, bars + B_QK);
            }
        } else {
            if (elect()) {
                if (pw & 2) {
                    if (pw & 1) { init(B_GO, B_Z, 1); init(B_RND, B_RND + 96, 12); mbar_init(bars + B_RND + 96, nlast); }
                    else        { init(B_F, B_GO, GW); init(B_FA, B_SENT, 8); mbar_init(bars + B_SENT, LW + 4); }
                } else          { init(B_A, B_F, 4); mbar_init(bars + B_S, 6); mbar_init(bars + B_VE, GW); mbar_init(bars + B_Z, AW); init(B_HV, B_RV + 8, 1); }
                asm volatile("fence.mbarrier_init.release.cluster;" ::: "memory");
            }
        }
        bar_arrive(4, LT + 128);
        bar_arrive(0, GT + 128);
        if (pw == 0 && rowcta && elect()) {
#pragma unroll
            for (int kq = 0; kq < 4; ++kq) mbar_expect(bars + B_K + kq * 8, KB + 4 * UNIT);
#pragma unroll
            for (int i = 7; i >= 0; --i) {
                const int kq = (XORD >> (4 * i)) & 3;
                if ((XORD >> (4 * i)) & 4) tma3d(sS + (kq == 3 ? A4 : 4 * kq) * UNIT, &tmWl, kq * 64, bars + B_K + kq * 8);
                else tma2d(sT + kq * KB, &tmX, kq * 64, node0, bars + B_K + kq * 8);
            }
            PROF(3);
            prefetch_map(&tmM); prefetch_map(&tmG); prefetch_map(&tmWv); prefetch_map(&tmV3); prefetch_map(&tmR);
        }
        if (pw >= 2 ? stage : pw && rowcta && lane < 10) pe = ldg_in(pw >= 2 ? (const char*)(p.esrc + (node0 + 32 * (pw - 2) + lane) * 4) : (const char*)(p.dis + node0 + lane * 8));
        auto load_units = [&](const CUtensorMap* tm, int kq, int slot) {
            if (elect()) { mbar_expect(bars + B_K + kq * 8, 4 * UNIT); tma3d(sS + slot * UNIT, tm, kq * 64, bars + B_K + kq * 8); }
        };
        const int v0 = pw ? pw - 2 : 2;
        auto tile_rows = [&](uint2 (&e)[6], int c) {
#pragma unroll
            for (int n = 0; n < 6; ++n) {
                const int v = min(v0 + 3 * n, 15);
                asm volatile("ld.shared.v2.u32 {%0, %1}, [%2];" : "=r"(e[n].x), "=r"(e[n].y) : "r"(bars + MI_ES + ((v >> 2) * 16 + c * 4 + (v & 3)) * 8) : "memory");
            }
        };
        auto stage_tiles = [&](const uint2 (&e)[6], int c) {
            mbar_wait(bars + (c ? B_F + 32 + c * 8 : T0BAR), 0);
            if (elect()) {
#pragma unroll
                for (int n = 0; n < 6; ++n) {
                    const int v = v0 + 3 * n;
                    if (n < 5 || v < 16) {
                        const uint32_t dst = sS + (A_TILES >> (8 * c) & 255) * UNIT + v * 2048, bar = bars + B_A + ((v & 12) + c) * 8;
                        mbar_expect(bar, 2048);
                        tma2d(dst, &tmG, 0, e[n].x & 0xffffu, bar);        tma2d(dst + 512, &tmG, 0, e[n].x >> 16, bar);
                        tma2d(dst + 1024, &tmG, 0, e[n].y & 0xffffu, bar); tma2d(dst + 1536, &tmG, 0, e[n].y >> 16, bar);
                    }
                }
            }
            if (pw == 2 && lane == 0) PROF(45 + c);
        };
        if (pw >= 2) asm volatile("st.shared.v2.u32 [%0], {%1, %2};" :: "r"(bars + MI_ES + ((pw - 2) * 32 + lane) * 8), "r"(pe.x | pe.y << 16), "r"(pe.z | pe.w << 16) : "memory");
        else if (pw == 1 && lane < 10) sts128(bars + MI_DIS + lane * 16, pe);
        {
            bar_sync(1, GT + 128);
            const int v = tid - AW * 32;
            const float* rp = (const float*)(smem + SM_X) + (v >> 3) * 32 + (((v & 7) * 4 + (v & 24)) & 31);
            const float4 v0 = *(const float4*)rp, v1 = *(const float4*)(rp + 512), v2 = *(const float4*)(rp + 1024), v3 = *(const float4*)(rp + 1536);
            p.M[(i0 + (v >> 3)) * 64 + (j0 >> 2) + (v & 7)] =
                make_uint2(pack_bf16((v0.x + v1.x) + (v2.x + v3.x), (v0.y + v1.y) + (v2.y + v3.y)),
                           pack_bf16((v0.z + v1.z) + (v2.z + v3.z), (v0.w + v1.w) + (v2.w + v3.w)));
            warp_arrive(bars + B_SENT);
        }
        if (pw != 1 && rowcta) {
            uint2 e[4][6];
#pragma unroll
            for (int c = 0; c < 4 - G3; ++c) tile_rows(e[c], c);
            mbar_wait(bars + B_EPO, 0);
            mbar_wait(bars + B_F, 0);
#pragma unroll 1
            for (int c = 0; c < 4 - G3; ++c) {
                if (pw == 0 && c == 0) {
                    mbar_wait(bars + B_CGO, 0);
                    wait_count(p.sync + SY_M, (lds32(bars + MI_EPOCH) + 1) * NCTA);
                    fence_async_gmem();
                    if (lane == 0) PROF(2);
                    load_units(&tmM, 0, A0);
                    if (lane == 0) PROF(39);
                    mbar_wait(bars + B_F + 8, 0);  load_units(&tmM, 1, A1);
                    mbar_wait(bars + B_F + 16, 0); load_units(&tmM, 2, A2);
                    warp_arrive(bars + B_MI);
                    if (lane == 0) PROF(40);
                }
                if (pw == 0 && c == 1) { mbar_wait(bars + B_F + 32, 0); load_units(&tmM, 3, A0); }
                if (stage) stage_tiles(e[0], c);
#pragma unroll
                for (int n = 0; n < 6; ++n) { e[0][n] = e[1][n]; e[1][n] = e[2][n]; if (!G3) e[2][n] = e[3][n]; }
            }
        }
        if (pw == 0) {
            if (rowcta) {
                if (HRW == 1) mbar_wait(bars + B_HR, 0);
                mbar_wait(bars + B_FA, 0);      fence_async_smem();  load_units(&tmWv, 0, A3);
                if (HRW == 2) mbar_wait(bars + B_HR, 0);
                mbar_wait(bars + B_FA + 8, 0);  fence_async_smem();  load_units(&tmWv, 1, A1);
                mbar_wait(bars + B_FA + 16, 0); fence_async_smem();  load_units(&tmWv, 2, A2);
                mbar_wait(bars + B_HR, 0);
                mbar_wait(bars + B_XF, 0);      fence_async_smem();
                if (elect()) {
                    mbar_expect(bars + B_K + 24, 4 * UNIT);
#pragma unroll
                    for (int ks = 0; ks < 4; ++ks) tma3d(sS + (A5 + ks) * UNIT, &tmV3, 192 + ks * 16, bars + B_K + 24);
                }
                if (lane == 0) PROF(5);
            }
        } else if (pw == 1) {
            mbar_wait(bars + B_SENT, 0);
            if (elect()) { PROF(38); red_release(p.sync + SY_M); PROF(1); mbar_arrive(bars + B_CGO); }
            if (VPF && lane < 8) asm volatile("prefetch.global.L2 [%0];" :: "l"(p.wv + (cta * 8 + lane) * 128));
            mbar_wait(bars + B_EPO, 0);
            if (rowcta) {
                mbar_wait(bars + B_HS, 0);
                mbar_wait(bars + B_LF, 0);
                fence_async_smem();
                mbar_wait(bars + B_MI, 0);
                if (HGATE >= 0) mbar_wait(bars + B_K + HGATE * 8, 1);
                uint32_t tn = clk();
#pragma unroll 1
                for (int s = 0; s < 32; s += 2) {
                    wait_clk(tn); tn += HPER;
                    if (elect()) {
                        bulk_store(p.H + s * N + node0, sS + A4 * UNIT + s * 1280, 1280);
                        bulk_store(p.H + (s + 1) * N + node0, sS + A4 * UNIT + s * 1280 + 1280, 1280);
                    }
                }
#pragma unroll 1
                for (int z = cta; z < ER * AW * 16; z += RCTA) {
                    wait_clk(tn); tn += HPER;
                    if (elect()) bulk_store(p.out + ((z & 3) * (UPQ * 16) + (z >> 2) * 4) * 32, sb + X_ZERO, 2048);
                }
                if (elect()) {
                    bulk_commit();
                    asm volatile("cp.async.bulk.wait_group 0;" ::: "memory");
                    PROF(43);
                    fence_async_gmem();
                    red_release(p.sync + SY_H);
                    mbar_arrive(bars + B_HR);
                    PROF(31);
                }
            }
            wait_count(p.sync + SY_H, (lds32(bars + MI_EPOCH) + 1) * RCTA);
            fence_async_gmem();
            warp_arrive(bars + B_HV);
            if (lane == 0) PROF(6);
            const char* hs = (const char*)(p.H + slice * N) - 128;
            auto chunk = [&](int bar, int lo, int hi) {
                if (rowcta && bar) mbar_wait(bars + bar, 0);
                if (bar >= B_FA) fence_async_smem();
                if (lo == 128) { if (lane < 8) sts128(sS + lane * 16, make_uint4(0, 0, 0, 0)); __syncwarp(); }
                if (elect()) { mbar_expect(bars + B_S, hi - lo); bulk_load(sS + lo, hs + lo, hi - lo, bars + B_S); }
            };
            chunk(0, A4 * UNIT, A5 * UNIT);
            chunk(B_FA + 24, 128, 4 * UNIT);
            chunk(B_F + 64, A3 * UNIT, (A3 + 4) * UNIT);
            chunk(B_F + 72, A1 * UNIT, (A1 + 4) * UNIT);
            chunk(B_F + 80, A2 * UNIT, (A2 + 4) * UNIT);
            chunk(B_F + 88, A5 * UNIT, SLICE_END);
            if (lane == 0) PROF(7);
        } else {
            mbar_wait(bars + B_EPO, 0);
            const uint32_t epoch1 = lds32(bars + MI_EPOCH) + 1;
            if (pw == 2) {
                if (rowcta) {
                    uint32_t early = 0;
#pragma unroll
                    for (int r = 0; r < 5; ++r) { const int u = cta * 5 + r; early |= (u - min(u / UPQ, 3) * UPQ < ER * AW) << r; }
                    auto put_r = [&](bool add) {
#pragma unroll 1
                        for (int r = 0; r < 5; ++r) {
                            const int u = cta * 5 + r;
                            if ((early >> r & 1) == add) {
                                if (elect()) {
#pragma unroll
                                    for (int kb = 0; kb < 4; ++kb) {
                                        if (add) tma2d_add(&tmR, sT + kb * KB + r * 2048, kb * 64, u * 16);
                                        else     tma2d_store(&tmR, sT + kb * KB + r * 2048, kb * 64, u * 16);
                                    }
                                }
                                if (RPER && add) wait_clk(clk() + RPER);
                            }
                        }
                        bulk_commit();
                    };
                    mbar_wait(bars + B_R, 0);
                    fence_async_smem();
                    put_r(false);
                    if (elect()) {
                        asm volatile("cp.async.bulk.wait_group 0;" ::: "memory");
                        fence_async_gmem();
                        p.sync[SY_SLOW + cta] = slow_cta();
                        red_release(p.sync + SY_R);
                        PROF(22);
                    }
                    mbar_wait(bars + B_S, 0);
                    put_r(true);
                    bulk_wait_read<0>();
                    if (lane == 0) PROF(41);
                }
                warp_arrive(bars + B_TF);
                wait_count(p.sync + SY_R, epoch1 * RCTA);
                fence_async_gmem();
                warp_arrive(bars + B_RV);
                if (lane == 0) PROF(23);
            } else {
                if (lane == 0) prefetch_map(&tmO);
                mbar_wait(bars + B_XF, 0);
                if (elect()) red_relaxed(p.sync + SY_L);
                wait_count(p.sync + SY_L, epoch1 * NCTA);
                warp_arrive(bars + B_GO);
                if (lane == 0) PROF(42);
                if (cta == 0 && lane < 16) *(volatile uint32_t*)(p.sync + lane * 32) = epoch1;
#pragma unroll 1
                for (int i = 0; i < 13; ++i) {
                    if (i == 2 * ER) mbar_wait(bars + B_RV, 0);
                    mbar_wait(bars + B_RND + i * 8, 0);
                    fence_async_smem();
                    if (elect()) {
                        tma2d_add(&tmO, sb + SM_X + i * 3072, slice * 8, quarter * (UPQ * 16) + i * 192);
                        if (i == 12 && quarter == 3) tma2d_add(&tmO, sb + SM_X + 13 * 3072, slice * 8, 3 * (UPQ * 16) + 13 * 192);
                    }
                    if (lane == 0 && !(i & 1)) PROF(53 + (i >> 1));
                }
                bulk_commit();
                if (lane == 0) PROF(8);
                bulk_wait_read<0>();
                if (lane == 0) PROF(9);
            }
        }
        if (pw < 2) {
            mbar_wait(bars + B_EPO, 0);
            mbar_wait(bars + B_XF, 0);
            const int novf = min(lds32(bars + MI_NOVF), (uint32_t)OVCAP);
#pragma unroll 1
            for (int o = OB * pw; o < novf; o += 2 * OB) {
                const int n = min(novf - o, OB);
                uint32_t w = lds32(bars + MI_OVF + (o + min(lane, n - 1)) * 4);
                int rk = 0;
#pragma unroll 1
                for (int j = 0; j < n; ++j) { const uint32_t y = __shfl_sync(0xffffffffu, w, j); rk += y < w || (y == w && j < lane); }
                if (lane < n) sts32(bars + MI_OVF + (o + rk) * 4, w);
                __syncwarp();
                w = lds32(bars + MI_OVF + (o + min(lane, n - 1)) * 4);
                const uint32_t more = __ballot_sync(0xffffffffu, (((__shfl_down_sync(0xffffffffu, w, 1) ^ w) >> 14) == 0) & (lane + 1 < n));
                const uint32_t f = __ldg((const unsigned short*)p.dis + (w >> 14)) * 0x10001u;
                mbar_wait(bars + B_HV, 0);
                uint4 v[OB];
#pragma unroll
                for (int i = 0; i < OB; i += 3) {
                    if (i < n) {
#pragma unroll
                        for (int j = i; j < i + 3; ++j) {
                            const uint32_t s = __shfl_sync(0xffffffffu, w, j) & 0x3fffu;
                            v[j] = make_uint4(0, 0, 0, 0);
                            if (j < n) v[j] = ldg_sc(p.H + lane * N + s);
                        }
#pragma unroll
                        for (int j = i; j < i + 3; ++j) {
                            const uint32_t fj = __shfl_sync(0xffffffffu, f, j);
                            v[j] = make_uint4(hmul2(v[j].x, fj), hmul2(v[j].y, fj), hmul2(v[j].z, fj), hmul2(v[j].w, fj));
                            if (j && (more >> (j - 1) & 1)) v[j] = make_uint4(hadd2(v[j].x, v[j - 1].x), hadd2(v[j].y, v[j - 1].y), hadd2(v[j].z, v[j - 1].z), hadd2(v[j].w, v[j - 1].w));
                        }
                    }
                }
                mbar_wait(bars + B_RV, 0);
                const uint32_t go = __ballot_sync(0xffffffffu, lane < n && !ld_relaxed(p.sync + SY_SLOW + (w >> 14) / NPC)) & ~more;
#pragma unroll
                for (int j = 0; j < OB; ++j)
                    if (go >> j & 1) red_row(p.out + (__shfl_sync(0xffffffffu, w, j) >> 14) * 32 + lane, v[j]);
            }
            if (lane == 0) PROF(pw ? 48 : 44);
        }
    } else {
        const int g = lane >> 2, t = lane & 3;
        const int wi = warp < GW ? warp + LW : warp - GW;
        Unit x0, x1;
        const uint4* ip;
        auto fetch = [&](Unit& x, int j) { x.a = ld_relaxed4(ip + j * 64); x.b = ld_relaxed4(ip + j * 64 + 32); };
        auto fetch0 = [&]() { int l = lane; asm volatile("" : "+r"(l)); ip = p.idx + quarter * (UPQ * 64) + l; fetch(x0, wi); };
        if (warp < GW) {
            const int wg = warp >> 2, w4 = warp & 3;
            uint32_t h[20];
            sts32(bars + MI_TOUCH, (uint32_t)(uint64_t)p.dis ^ p.Ee);
            if (rowcta) {
#pragma unroll
                for (int j = 0; j < 10; ++j) h[j] = __ldg((const uint32_t*)p.dis + (node0 >> 1) + 4 * j + t);
            }
            bar_sync(0, GT + 128);
            {
                float* red = (float*)(smem + SM_X);
                const int cw = (w4 - wg * (MW == 1 ? 1 : MW == 2 ? 2 : 0)) & 3;
                if (cw < MW) {
                    const uint32_t qa = sS + A3 * UNIT + wg * 2048 + (lane & 15) * 128 + (((lane >> 4) ^ (lane & 7)) << 4);
                    const uint32_t ka = sS + (A3 + 1) * UNIT + wg * 4096 + (cw * (32 / MW) + (lane & 7)) * 128 + (((lane >> 3) ^ (lane & 7)) << 4);
                    mbar_wait(bars + B_QK, 0);
                    __syncwarp();
                    if (tid == 0) PROF(33);
                    const uint4 a0 = ldsm4(qa), a1 = ldsm4(qa ^ 32), a2 = ldsm4(qa ^ 64), a3 = ldsm4(qa ^ 96);
                    uint4 bb[4 / MW][2];
#pragma unroll
                    for (int nb = 0; nb < 4 / MW; ++nb) { bb[nb][0] = ldsm4(ka + nb * 1024); bb[nb][1] = ldsm4((ka ^ 64) + nb * 1024); }
#pragma unroll
                    for (int nb = 0; nb < 4 / MW; ++nb) {
                        const uint4 b0 = bb[nb][0], b1 = bb[nb][1];
                        float c[4] = {0.f, 0.f, 0.f, 0.f}, e[4] = {0.f, 0.f, 0.f, 0.f};
                        mma16816(c, a0.x, a0.y, a0.z, a0.w, b0.x, b0.y); mma16816(e, a1.x, a1.y, a1.z, a1.w, b0.z, b0.w);
                        mma16816(c, a2.x, a2.y, a2.z, a2.w, b1.x, b1.y); mma16816(e, a3.x, a3.y, a3.z, a3.w, b1.z, b1.w);
                        float* rp = red + (wg * 16 + g) * 32 + (((cw * (4 / MW) + nb + g) & 3) * 8) + 2 * t;
                        *(float2*)rp         = make_float2(c[0] + e[0], c[1] + e[1]);
                        *(float2*)(rp + 256) = make_float2(c[2] + e[2], c[3] + e[3]);
                    }
                }
                bar_arrive(1, GT + 128);
            }
            if (rowcta) {
                float d[40];
                const uint32_t uw = sS + wg * UNIT, fb = bars + B_F;
                fence_async_smem();
                mbar_wait(bars + B_SENT, 0);
                if (tid == 0) PROF(35);
                gemm_quarter<0>(d, uw + A0 * UNIT, sT, bars + B_K, 0);
                if (tid == 0) PROF(10);
                gemm_quarter<1>(d, uw + A1 * UNIT, sT, bars + B_K, 0, fb);
                gemm_quarter<2>(d, uw + A2 * UNIT, sT, bars + B_K, 0, fb + 8);
                gemm_quarter<3>(d, uw + A4 * UNIT, sT, bars + B_K, 0, fb + 16);
                wg_wait<0>(); warp_arrive(fb + 24);
                if (tid == 0) PROF(11);
#pragma unroll
                for (int j = 9; j >= 0; --j) {
                    const float s0 = blo(h[j]), s1 = bhi(h[j]);
                    h[2 * j + 1] = pack_bf16(d[4 * j + 2] * s0, d[4 * j + 3] * s1);
                    h[2 * j]     = pack_bf16(d[4 * j] * s0, d[4 * j + 1] * s1);
                }
                mbar_wait(fb + 24, 0);
                __syncwarp();
                {
                    const uint32_t sa = sS + A4 * UNIT + warp * 2560 + (lane & 8) * 160 + (lane >> 4) * 128 + (lane & 7) * 16;
#pragma unroll
                    for (int i = 0; i < 5; ++i) stsm4t(sa + i * 256, h[4 * i], h[4 * i + 1], h[4 * i + 2], h[4 * i + 3]);
                }
                warp_arrive(bars + B_HS);
                if (tid == 0) PROF(60);
                uint4 e3 = make_uint4(0, 0, 0, 0);
                if (G3 && stage) e3 = ldg_in(p.esrc + (node0 + 16 * wg + 12 + w4) * 4);
                gemm_quarter<0>(d, uw + A0 * UNIT, sT, bars + B_K, 1);
                if (tid == 0) PROF(12);
                gemm_quarter<1>(d, uw + A1 * UNIT, sT, bars + B_K, 1, fb + 32);
                gemm_quarter<2>(d, uw + A2 * UNIT, sT, bars + B_K, 1, fb + 40);
                mbar_wait(bars + B_LF, 0);
                const uint32_t ebad = lds32(bars + MI_EBAD);
                gemm_quarter<3>(d, uw + A0 * UNIT, sT, bars + B_K, 1, fb + 48);
                if (tid == 0) PROF(13);
                wg_wait<0>(); warp_arrive(fb + 56);
                if (tid == 0) PROF(14);
                pack_acc(h, d);
                mbar_wait(fb + 32 + wg * 8, 0);
                __syncwarp();
                store_tile(h, sT, wg, w4, lane);
                warp_arrive(bars + B_Q);
                auto stage3 = [&]() {
                    mbar_wait(fb + 56, 0);
                    if (G3 && stage && elect()) {
                        const uint32_t dst = uw + A0 * UNIT + w4 * 2048, bar = bars + B_A + (4 * wg + 3) * 8;
                        mbar_expect(bar, 2048);
                        tma2d(dst, &tmG, 0, e3.x, bar);        tma2d(dst + 512, &tmG, 0, e3.y, bar);
                        tma2d(dst + 1024, &tmG, 0, e3.z, bar); tma2d(dst + 1536, &tmG, 0, e3.w, bar);
                    }
                };
                const uint32_t rows = uw + (w4 & 1) * 4096 + (lane & 4) * 512 + (lane & 8) * 64 + (((lane ^ (lane >> 2 & 4)) & 7) << 4);
#pragma unroll AUNR
                for (int c2 = 0; c2 < 4; c2 += 2) {
                    const int c = (w4 >> 1) + c2;
                    const int n = 16 * wg + 4 * c + 2 * (w4 & 1);
                    if (stage) mbar_wait(bars + B_A + (4 * wg + c) * 8, 0);
                    if (tid == 0) PROF(c ? 50 : 15);
                    if (tid == 96) PROF(c == 1 ? 51 : 52);
                    if (!ebad) {
                        const uint32_t ra = rows + (A_TILES >> (8 * c) & 255) * UNIT;
                        uint4 r[2][4];
#pragma unroll
                        for (int kb = 0; kb < 4; ++kb) { r[0][kb] = ldsm4(ra + kb * 128); r[1][kb] = ldsm4(ra + 1024 + kb * 128); }
                        warp_arrive(bars + B_FA + c * 8);
                        if (c2 == 0) { stage3(); mbar_wait(bars + B_Q, 0); }
                        __syncwarp();
                        attention_frags(r, sT, n, lane);
                    } else {
                        warp_arrive(bars + B_FA + c * 8);
                        if (c < 2) stage3();
                        mbar_wait(bars + B_Q, 0);
                        attention_generic(p, sT, n, node0 + n, lane); attention_generic(p, sT, n + 1, node0 + n + 1, lane);
                    }
                }
                fence_async_smem();
                warp_arrive(bars + B_Z);
                if (tid == 0) PROF(16);
                mbar_wait(bars + B_K, 0);
                if (tid == 0) PROF(17);
                gemm_quarter<0>(d, uw + A3 * UNIT, sT, bars + B_Z, 0);
                gemm_quarter<1>(d, uw + A1 * UNIT, sT, bars + B_K, 0, fb + 64);
                gemm_quarter<2>(d, uw + A2 * UNIT, sT, bars + B_K, 0, fb + 72);
                bool early = false;
                if (EFETCH == 1) { early = mbar_test(bars + B_GO, 0); if (early) fetch0(); }
                {
                    mbar_wait(bars + B_K + 24, 0);
                    __syncwarp();
                    const uint32_t a = desc_lo(sS + A5 * UNIT + wg * 2048), b = desc_lo(sT) + ((3 * KB) >> 4);
                    wg_fence();
                    wgmma80<false>(d, a, b);            wg_commit(); wg_wait<1>(); warp_arrive(fb + 80);
                    wgmma80<false>(d, a + 512, b + 2);  wg_commit(); wg_wait<1>(); warp_arrive(fb + 88);
                    if (EFETCH == 2) { early = mbar_test(bars + B_GO, 0); if (early) fetch0(); }
                    wgmma80<false>(d, a + 1024, b + 4);
                    wgmma80<false>(d, a + 1536, b + 6); wg_commit();
                    if (EFETCH == 3) { early = mbar_test(bars + B_GO, 0); if (early) fetch0(); }
                }
                wg_wait<0>(); warp_arrive(bars + B_VE);
                if (tid == 0) PROF(18);
                pack_acc(h, d);
                mbar_wait(wg == 3 ? bars + B_VE : fb + 64 + wg * 8, 0);
                __syncwarp();
                store_tile(h, sT, wg, w4, lane);
                warp_arrive(bars + B_R);
                if (!early) { mbar_wait(bars + B_GO, 0); fetch0(); }
                if (tid == 0) PROF(19);
            } else {
                mbar_wait(bars + B_GO, 0);
                fetch0();
            }
        } else {
            const int lw = warp - GW, tl = tid - GT;
            uint32_t dd[5], ss[5];
            const int e0 = cta * p.chunk;
            {
                const int last = max(p.Efast - 2, 0);
                const uint32_t ea = min(e0 + 2 * tl, last), eb = min(e0 + 2 * tl + 2 * LT, last), ec = min(e0 + tl + 4 * LT, last + 1);
                const int2 d0 = __ldg((const int2*)(p.dst + ea)), d1 = __ldg((const int2*)(p.dst + eb));
                dd[4] = __ldg(p.dst + ec);
                const int2 s0 = __ldg((const int2*)(p.src + ea)), s1 = __ldg((const int2*)(p.src + eb));
                ss[4] = __ldg(p.src + ec);
                dd[0] = d0.x; dd[1] = d0.y; dd[2] = d1.x; dd[3] = d1.y; ss[0] = s0.x; ss[1] = s0.y; ss[2] = s1.x; ss[3] = s1.y;
            }
            const uint32_t epoch = ld_relaxed(p.sync + (cta & 15) * 32);
            int4 ed = make_int4(0, 0, 0, 0), es = make_int4(0, 0, 0, 0);
            if (stage) {
                ed = __ldg((const int4*)p.edst4 + (uint32_t)(node0 + min(tl, NPC - 1)));
                es = __ldg((const int4*)p.esrc + (uint32_t)(node0 + 64 + (tl >> 4)));
            }
            {
                const uint32_t lo = (tl & 3) * 0x40004000u, hi = (NPC * 2 + (cta & 7)) * 0x010101u;
#pragma unroll
                for (int r = 0; r < 2; ++r) {
                    sts128(sb + X_OUT + (tl + r * LT) * 16, make_uint4(lo, lo, (lo & 0xffffu) | hi << 16, hi));
                    sts128(sb + X_IMG + (tl + r * LT) * 16, make_uint4(0, 0, 0, 0));
                }
            }
            if (tl < 32) sts128(bars + MI_PCNT + tl * 16, make_uint4(0, 0, 0, 0));
            if (tl == 32) { sts32(bars + MI_SLOW, p.chunk == 0); sts32(bars + MI_EBAD, !p.edst4); sts32(bars + MI_NOVF, 0); sts32(bars + MI_FLAGS, 0); }
            bar_sync(2, LT);
            if (tl == 0) PROF(34);
            const int zero = lds32(bars + MI_PCNT + 127 * 4);
            const int ne = min(p.chunk, p.Efast - e0) + zero;
            uint32_t q[5], nx = 0, ox = 0;
            {
                uint32_t c[5];
#pragma unroll
                for (int k = 0; k < 5; ++k) {
                    dd[k] = (k < 4 ? 2 * tl + (k >> 1) * 2 * LT : tl + 4 * LT) < ne ? dd[k] : (RCTA + (lane & 1)) * NPC;
                    c[k] = dd[k] / NPC;
                    q[k] = atoms_add(bars + MI_PCNT + c[k] * 4, c[k] < RCTA);
                }
                if (tl == 0) PROF(36);
#pragma unroll
                for (int k = 0; k < 5; ++k) {
                    const uint32_t w = (((dd[k] - c[k] * NPC) * 8 + (ss[k] & 7u)) << 14) + ss[k] + 8;
                    uint32_t sl = (q[k] >> 2) + (SROT ? (c[k] >> 3) & 3u : 0u);
                    if (SROT) sl = min(sl, sl - 5);
                    const uint32_t ca = sb + X_OUT + c[k] * 64 + ((q[k] + (c[k] >> 1)) & 3u) * 16 + sl;
                    if (q[k] < CELLN) { sts16(ca + sl, w); asm volatile("st.shared.u8 [%0 + 10], %1;" :: "r"(ca), "r"(w >> 16) : "memory"); }
                    nx += q[k] >= CELLN;
                }
                if (nx) ox = atoms_add(bars + MI_NOVF, nx);
                const int nz = node0 + tl + zero;
                if (stage && tl < NPC && ((ed.x != nz) | (ed.y != nz) | (ed.z != nz) | (ed.w != nz))) sts32(bars + MI_FLAGS, W_EBAD);
            }
            if (tl == 0) PROF(37);
            bar_sync(4, LT + 128);
            if (tl == 0) PROF(24);
            const uint32_t tag = ((epoch + zero) % 31u + 1u) << 27;
            {
                const uint32_t fl = lds32(bars + MI_FLAGS) | tag | (lds32(bars + MI_NOVF) > OVCAP / 2 ? W_OVF : 0u);
                uint4* const gp = p.cells + ((tl >> 2) * NCTA + cta) * 4 + (tl & 3);
#pragma unroll
                for (int r = 0; r < 2; ++r) {
                    uint4 w = lds128(sb + X_OUT + (tl + r * LT) * 16);
                    w.w |= fl;
                    if (r == 0 || tl + LT < RCTA * 4) gp[r * (LT / 4) * NCTA * 4] = w;
                }
            }
            warp_arrive(bars + B_SENT);
            if (tl == 0) { sts32(bars + MI_EPOCH, epoch); mbar_arrive(bars + B_EPO); }
            if (tl == 0) PROF(25);
#pragma unroll
            for (int k = 0; k < 5; ++k) {
                if (q[k] >= CELLN) sts32(bars + MI_OVF + min(ox, (uint32_t)OVCAP - 1) * 4, dd[k] << 14 | ss[k]);
                ox += q[k] >= CELLN;
            }
            uint4 r[4][2];
            auto load_rows = [&]() {
                if (stage) {
                    const char* xl = p.x + (lane & 15) * 16;
                    const char* r0 = row_ptr(xl, es.x); const char* r1 = row_ptr(xl, es.y); const char* r2 = row_ptr(xl, es.z); const char* r3 = row_ptr(xl, es.w);
                    r[0][0] = ldg_in(r0); r[0][1] = ldg_in(r0 + 256); r[1][0] = ldg_in(r1); r[1][1] = ldg_in(r1 + 256);
                    r[2][0] = ldg_in(r2); r[2][1] = ldg_in(r2 + 256); r[3][0] = ldg_in(r3); r[3][1] = ldg_in(r3 + 256);
                }
            };
            auto attend = [&]() {
                mbar_wait(bars + B_Q, 0);
                __syncwarp();
                if (!lds32(bars + MI_EBAD)) attention_chunks(r, sT, 64 + 2 * lw, lane);
                else { attention_generic(p, sT, 64 + 2 * lw, node0 + 64 + 2 * lw, lane); attention_generic(p, sT, 65 + 2 * lw, node0 + 65 + 2 * lw, lane); }
                fence_async_smem();
                warp_arrive(bars + B_Z);
                if (tl == 0) PROF(32);
            };
            if (rowcta) {
                mbar_wait(bars + B_SENT, 0);
                if (tl == LT - 1) sts32(sb + X_TAB + NPC * 64, 64);
                if (tl < 128) sts128(sb + X_ZERO + tl * 16, make_uint4(0, 0, 0, 0));
                uint4 c0, c1;
                const uint4* cp = p.cells + cta * (NCTA * 4) + tl;
                mbar_wait(bars + B_CGO, 0);
#pragma unroll 1
                for (int it = 0;; ++it) {
                    c0 = ld_relaxed4(cp); c1 = ld_relaxed4(cp + LT);
                    if (!__any_sync(0xffffffffu, ((c0.w ^ tag) | (c1.w ^ tag)) >> 27) || it >= SPIN_LIMIT) break;
                }
                if (tl == 0) PROF(26);
                if ((c0.w | c1.w) & W_OVF)  sts32(bars + MI_SLOW, 1);
                if ((c0.w | c1.w) & W_EBAD) sts32(bars + MI_EBAD, 1);
                uint32_t w[10] = {__byte_perm(c0.x, c0.z, 0x6610), __byte_perm(c0.x, c0.z, 0x7732), __byte_perm(c0.y, c0.w, 0x4410), __byte_perm(c0.y, c0.w, 0x5532), __byte_perm(c0.z, c0.w, 0x6610),
                                  __byte_perm(c1.x, c1.z, 0x6610), __byte_perm(c1.x, c1.z, 0x7732), __byte_perm(c1.y, c1.w, 0x4410), __byte_perm(c1.y, c1.w, 0x5532), __byte_perm(c1.z, c1.w, 0x6610)};
                {
                    uint32_t c[10];
#pragma unroll
                    for (int m = 0; m < 10; ++m) {
                        const uint32_t a = (w[m] >> 12) & 0xffcu;
                        c[m] = atoms_add(sb + X_CNT + a, a < NPC * 32);
                        w[m] = (w[m] & 0x3fffu) + (a << 15);
                    }
#pragma unroll
                    for (int m = 0; m < 10; ++m) w[m] += (c[m] > 7 ? 0x20000u : c[m]) << 14;
                }
                bar_sync(2, LT);
                if (tl == 0) { mbar_arrive(bars + B_LF); PROF(27); }
                if (lw < 3) {
                    const int d0 = min(tl, NPC - 8 + (tl & 7));
                    const int dl = d0 ^ ((d0 >> 3) & 1);
                    const uint4 n0 = lds128(sb + X_CNT + dl * 32), n1 = lds128(sb + X_CNT + dl * 32 + 16);
                    uint32_t pk = min(n0.x, 8u) + (min(n0.y, 8u) << 4) + (min(n0.z, 8u) << 8) + (min(n0.w, 8u) << 12) +
                                  (min(n1.x, 8u) << 16) + (min(n1.y, 8u) << 20) + (min(n1.z, 8u) << 24) + (min(n1.w, 8u) << 28);
                    pk = __funnelshift_r(pk, pk, 4 * lane);
                    uint32_t du = 0xf0000000u, ru = 0, b[8] = {0, 0, 0, 0, 0, 0, 0, 0};
                    auto code2 = [&](uint32_t b0, uint32_t b1) {
                        return __byte_perm(__float_as_uint(__uint_as_float(b0) * 8388608.f), __float_as_uint(__uint_as_float(b1) * 8388608.f), 0x7632);
                    };
                    uint32_t ta = (lane + 7) * 8;
                    auto pass_on = [&]() {
                        ru = __shfl_sync(0xffffffffu, ru, lane + 1, 8);
                        const uint32_t t0 = (code2(b[0], b[2]) >> 7) + code2(b[1], b[3]) * 2, t1 = (code2(b[4], b[6]) >> 7) + code2(b[5], b[7]) * 2;
                        asm volatile("st.shared.v2.u32 [%0], {%1, %2};" :: "r"(sb + X_TAB + ((dl * 64) | (ta & 56))), "r"(t0), "r"(t1) : "memory");
                        ta += 8;
                    };
                    auto take = [&](uint32_t& m, uint32_t& bit, uint32_t n, int c) {
                        asm("{\n.reg .pred p;\n.reg .b32 u;\nsetp.gt.u32 p, %2, %3;\nadd.u32 u, %0, -1;\nlop3.b32 %1, %0, u, 0, 0x30;\n@p and.b32 %0, %0, u;\n}"
                            : "+r"(m), "=r"(bit) : "r"(n), "r"(c));
                    };
#pragma unroll 1
                    for (int k = 0; k < 8; ++k) {
                        const uint32_t n = pk & 15u;
                        const bool big = __any_sync(0xffffffffu, n > 6);
                        pk >>= 4;
                        pass_on();
                        const uint32_t fr = ~(du | ru);
                        uint32_t m = fr;
#pragma unroll
                        for (int c = 0; c < 6; ++c) take(m, b[c], n, c);
                        if (big) { take(m, b[6], n, 6); take(m, b[7], n, 7); }
                        du |= m ^ fr;
                        ru |= m ^ fr;
                    }
                    pass_on();
                    sts32(sb + X_RU + d0 * 4, ru);
                }
                if (tl == 0) PROF(49);
                if (LGATE >= 0) { mbar_wait(bars + B_MI, 0); mbar_wait(bars + B_K + LGATE * 8, 1); }
                load_rows();
                bar_sync(2, LT);
                if (tl == 0) PROF(28);
                const int v = LT - 1 - tl;
                if (lw >= 6 && v < 40) {
                    const uint4 b = lds128(sb + X_RU + (v >> 2) * 32), e = lds128(sb + X_RU + (v >> 2) * 32 + 16);
                    const uint32_t f2 = b.x & b.y & b.z & b.w;
                    const uint32_t s0 = (f2 & e.x) | (~f2 & b.x), s1 = (f2 & e.y) | (~f2 & b.y), s2 = (f2 & e.z) | (~f2 & b.z);
                    const uint32_t f1 = s0 & s1, f0 = (f1 & s2) | (~f1 & s0);
                    uint32_t u[4];
#pragma unroll
                    for (int k = 0; k < 4; ++k) {
                        const int sh = (v & 3) * 8 + 2 * k;
                        u[k] = ((((f0 >> sh) & 3u) * 0x8001u) & 0x10001u) + ((((f1 >> sh) & 3u) * 0x10002u) & 0x20002u) + ((((f2 >> sh) & 3u) * 0x20004u) & 0x40004u);
                    }
                    sts128(sb + X_DEF + v * 16, make_uint4(u[0], u[1], u[2], u[3]));
                }
                {
                    uint32_t rd[10];
#pragma unroll
                    for (int m = 0; m < 10; ++m) asm volatile("ld.shared.u8 %0, [%1];" : "=r"(rd[m]) : "r"(sb + X_TAB + min(w[m] >> 14, NPC * 64u)) : "memory");
#pragma unroll
                    for (int m = 0; m < 10; ++m) {
                        rd[m] -= 1;
                        if (rd[m] < 48) sts16(sb + X_IMG + ((w[m] >> 14) & ~63u) + min(rd[m], 31u) * 2, w[m] & 0x3fffu);
                        w[m] |= rd[m] & 0x80000000u;
                    }
                    if (__any_sync(0xffffffffu, (int)(w[0] | w[1] | w[2] | w[3] | w[4] | w[5] | w[6] | w[7] | w[8] | w[9]) < 0)) {
                        uint32_t n = 0;
#pragma unroll
                        for (int m = 0; m < 10; ++m) n += w[m] >> 31;
                        uint32_t o = atoms_add(bars + MI_NOVF, n);
#pragma unroll
                        for (int m = 0; m < 10; ++m) {
                            if ((int)w[m] < 0) sts32(bars + MI_OVF + min(o, (uint32_t)OVCAP - 1) * 4, ((w[m] >> 6) & 0x1fc000u) + (w[m] & 0x3fffu) + (node0 * 16384 - 8));
                            o += w[m] >> 31;
                        }
                    }
                }
                bar_sync(2, LT);
                if (tl == 0) PROF(29);
#pragma unroll 1
                for (int set = lw; set < 10; set += lw >= 3 && lw < 5 ? 5 : 10) publish(set);
            }
            warp_arrive(bars + B_XF);
            if (tl == 0) PROF(30);
            if (rowcta) attend();
            mbar_wait(bars + B_GO, 0);
            fetch0();
        }
        const uint32_t stg = sb + SM_X + (lane & 15) * 16;
        const uint32_t lt = list_tag(lds32(bars + MI_EPOCH)), base = sS - (lt & 0xffffu) * 16;
        const int nu = UPQ + (quarter == 3);
        int u = wi;
        auto unit = [&](Unit& c, Unit& n) {
#pragma unroll 1
            for (int it = 0;; ++it) {
                if (!__any_sync(0xffffffffu, unit_stale(c, lt) > (it < SPIN_LIMIT ? 0u : 0xffffu))) break;
                fetch(c, u);
            }
            if (u >= 4 * AW) { mbar_wait(bars + B_TF, 0); __syncwarp(); }
            if (u + AW < nu) fetch(n, u + AW);
            agg_unit(c, base, stg + u * 256, lt);
            warp_arrive(bars + B_RND + min((u * 171) >> 11, 12) * 8);
            u += AW;
        };
        mbar_wait(bars + B_S, 0);
        if (rowcta) mbar_wait(bars + B_VE, 0);
        __syncwarp();
        if (tid == 0) PROF(20);
        if (tid == GT) PROF(4);
#pragma unroll 1
        for (;;) {
            unit(x0, x1);
            if (u >= nu) break;
            unit(x1, x0);
            if (u >= nu) break;
        }
        if (WPROF) { if (lane == 0) PROF(24 + wi); } else if (tid == 0) PROF(21);
        if (rowcta && slow_cta()) { mbar_wait(bars + B_RV, 0); local_generic(p, node0, wi, lane); }
    }
    PROF_FLUSH();
}

typedef CUresult (*EncodeFn)(CUtensorMap*, CUtensorMapDataType, cuuint32_t, void*, const cuuint64_t*, const cuuint64_t*,
                             const cuuint32_t*, const cuuint32_t*, CUtensorMapInterleave, CUtensorMapSwizzle,
                             CUtensorMapL2promotion, CUtensorMapFloatOOBfill);

static void make_map(EncodeFn enc, CUtensorMap* m, const void* ptr, int rows, int box_cols, int box_rows) {
    cuuint64_t dims[2] = {(cuuint64_t)D, (cuuint64_t)rows};
    cuuint64_t strides[1] = {(cuuint64_t)D * 2};
    cuuint32_t box[2] = {(cuuint32_t)box_cols, (cuuint32_t)box_rows};
    cuuint32_t es[2] = {1u, 1u};
    enc(m, CU_TENSOR_MAP_DATA_TYPE_BFLOAT16, 2, const_cast<void*>(ptr), dims, strides, box, es, CU_TENSOR_MAP_INTERLEAVE_NONE,
        box_cols == 64 ? CU_TENSOR_MAP_SWIZZLE_128B : CU_TENSOR_MAP_SWIZZLE_NONE,
        box_cols == 64 ? PROMO : CU_TENSOR_MAP_L2_PROMOTION_NONE, CU_TENSOR_MAP_FLOAT_OOB_FILL_NONE);
}
static void make_map3(EncodeFn enc, CUtensorMap* m, const void* ptr, int rows, int box_rows) {
    cuuint64_t dims[3] = {64, (cuuint64_t)rows, 4};
    cuuint64_t strides[2] = {(cuuint64_t)D * 2, 128};
    cuuint32_t box[3] = {64u, (cuuint32_t)box_rows, 4u};
    cuuint32_t es[3] = {1u, 1u, 1u};
    enc(m, CU_TENSOR_MAP_DATA_TYPE_BFLOAT16, 3, const_cast<void*>(ptr), dims, strides, box, es, CU_TENSOR_MAP_INTERLEAVE_NONE,
        CU_TENSOR_MAP_SWIZZLE_128B, CU_TENSOR_MAP_L2_PROMOTION_L2_256B, CU_TENSOR_MAP_FLOAT_OOB_FILL_NONE);
}

}

extern "C" void kernel_launch(void* const* d_in, const int* in_sizes, int n_in, void* d_out, int out_size) {
    using namespace gk;
    (void)n_in; (void)out_size;
    static EncodeFn enc = nullptr;
    static void *m_ptr, *cells_ptr, *sync_ptr, *h_ptr, *idx_ptr;
    if (!enc) {
        void* fn = nullptr;
        cudaDriverEntryPointQueryResult qr;
        cudaGetDriverEntryPoint("cuTensorMapEncodeTiled", &fn, cudaEnableDefault, &qr);
        enc = (EncodeFn)fn;
        cudaGetSymbolAddress(&m_ptr, g_M);
        cudaGetSymbolAddress(&cells_ptr, g_cells);
        cudaGetSymbolAddress(&sync_ptr, g_sync);
        cudaGetSymbolAddress(&h_ptr, g_H);
        cudaGetSymbolAddress(&idx_ptr, g_idx);
        cudaFuncSetAttribute(fused_kernel, cudaFuncAttributeMaxDynamicSharedMemorySize, SM_ALLOC);
    }
    if (in_sizes[5] != N || in_sizes[0] != N * D) return;
    Params p;
    p.src  = (const int*)d_in[1];
    p.dst  = (const int*)d_in[2];
    p.esrc = (const int*)d_in[3];
    p.edst = (const int*)d_in[4];
    p.sync = (uint32_t*)sync_ptr;
    p.x    = (const char*)d_in[0];
    p.dis  = (const __nv_bfloat16*)d_in[5];
    p.wv   = (const char*)d_in[9];
    p.cells = (uint4*)cells_ptr;
    p.H    = (uint4*)h_ptr;
    p.idx  = (uint4*)idx_ptr;
    p.M    = (uint2*)m_ptr;
    p.out  = (uint4*)d_out;
    p.E  = in_sizes[1];
    p.Ee = in_sizes[3];
    const int chunk = (((p.E + NCTA - 1) / NCTA) + 1) & ~1;
    const bool force_slow = chunk > 5 * LT || (p.E & 1) || p.E < 2;
    p.chunk = force_slow ? 0 : chunk;
    p.edst4 = p.Ee == 4 * N ? p.edst : nullptr;
    if (p.E < 2) p.src = p.dst = (const int*)d_in[0];
    p.Efast = force_slow ? 0 : p.E;

    CUtensorMap tmX, tmWl, tmM, tmWv, tmR, tmO, tmG, tmQ, tmK, tmV3;
    make_map(enc, &tmX, d_in[0], N, 64, NPC);
    make_map3(enc, &tmWl, d_in[6], D, 64);
    make_map3(enc, &tmM, m_ptr, D, 64);
    make_map3(enc, &tmWv, d_in[9], D, 64);
    make_map(enc, &tmR, d_out, N, 64, 16);
    make_map(enc, &tmO, d_out, N, 8, 192);
    make_map(enc, &tmG, d_in[0], N, 256, 1);
    make_map3(enc, &tmQ, d_in[7], D, 16);
    make_map3(enc, &tmK, d_in[8], D, 32);
    make_map3(enc, &tmV3, d_in[9], D, 16);
    fused_kernel<<<NCTA, NTHR, SM_ALLOC, cudaStreamPerThread>>>(p, tmX, tmWl, tmM, tmWv, tmR, tmO, tmG, tmQ, tmK, tmV3);
}
```

```cpp
#include <cuda_runtime.h>
#include <cuda_bf16.h>
#include <cuda.h>
#include <stdint.h>

#define PROFILE 0

namespace gk {

constexpr int N      = 10000;
constexpr int D      = 256;
constexpr int NPC    = 80;
constexpr int NCTA   = 128;
constexpr int RCTA   = N / NPC;
constexpr int NSET   = N / 8;
constexpr int GW     = 16;
constexpr int LW     = 8;
constexpr int AW     = GW + LW;
constexpr int GT     = GW * 32, LT = LW * 32;
constexpr int NTHR   = (AW + 4) * 32;
constexpr int UPQ    = 156;
constexpr int OVCAP  = 128;
#define SPINB 18
constexpr int SPIN_LIMIT = 1 << SPINB;

constexpr int KB      = NPC * 128;
constexpr int UNIT    = 8192;
constexpr int SM_S    = 0;
constexpr int SM_X    = 20 * UNIT;
constexpr int SM_T    = 23 * UNIT;
constexpr int SM_MISC = SM_T + 4 * KB;
constexpr int SM_END  = SM_MISC + 2464;
constexpr int SLICE_END = 128 + N * 16;
constexpr int X_OUT  = SM_X + UNIT;
constexpr int X_TAB  = X_OUT;
constexpr int X_RU   = X_TAB + NPC * 64 + 16;
constexpr int X_DEF  = X_RU + NPC * 4;
constexpr int X_ZERO = X_OUT + UNIT - 2048;
constexpr int X_IMG  = X_OUT + UNIT;
constexpr int X_CNT  = X_IMG + NPC * 64;
static_assert(X_DEF + 640 <= X_ZERO && X_CNT + NPC * 32 + 128 <= SM_T, "list scratch");
constexpr int B_K = 0, B_QK = 32, B_EPO = 40,
              B_A = 48,
              B_F = 176, B_HS = 272, B_Q = 280, B_R = 288,
              B_GO = 296, B_LF = 304, B_TF = 312,   B_CGO = 328, B_MI = 336, B_HR = 344,
              B_Z = 352,
              B_FA = 360, B_XF = 392, B_SENT = 400, B_S = 408, B_VE = 416,
              B_RND = 424;
constexpr int B_HV = 528, B_RV = 536;
constexpr int MI_EPOCH = 544, MI_EBAD = 548, MI_SLOW = 552, MI_NOVF = 556, MI_FLAGS = 560, MI_TOUCH = 564;
constexpr int MI_OVF  = 1280;
constexpr int MI_ES   = 768;
constexpr int MI_PCNT = 1792;
constexpr int MI_DIS  = 2304;
constexpr int A0 = 0, A1 = 4, A2 = 8, A3 = 12, A4 = 16, A5 = 19;
constexpr uint32_t A_TILES = A3 | A1 << 8 | A2 << 16 | A0 << 24;
#define ER 2
#define XORD 0x04156273
#define MW 2
#define OB 6
#define HPER 160

constexpr uint32_t W_OVF = 1u << 24, W_EBAD = 1u << 25;
constexpr int CELLN = 20;

__device__ uint4         g_cells[RCTA * NCTA * 4];
__device__ uint4         g_H[32 * N];
__device__ uint4         g_idx[NSET * 32];
__device__ __nv_bfloat16 g_M[D * D];
__device__ uint32_t      g_sync[24 * 32];
constexpr int SY_M = 16 * 32, SY_H = 17 * 32, SY_L = 18 * 32, SY_R = 19 * 32, SY_SLOW = 20 * 32;
#define PROF(i) do {} while (0)
#define PROF_FLUSH() do {} while (0)
constexpr int SM_ALLOC = SM_END;
static_assert(SM_ALLOC <= 232448, "shared memory");

struct Params {
    const int* src; const int* dst;
    uint32_t* sync;
    const int* esrc; const int* edst4;
    int Efast, chunk;
    const __nv_bfloat16* dis;
    const char* x; const char* wv;
    uint4* cells; uint2* M;
    uint4* idx; uint4* H; uint4* out;
    const int* edst;
    int E, Ee;
};

__device__ __forceinline__ uint32_t s32(const void* p) { return (uint32_t)__cvta_generic_to_shared(p); }
__device__ __forceinline__ void mbar_init(uint32_t a, uint32_t cnt) { asm volatile("mbarrier.init.shared.b64 [%0], %1;" :: "r"(a), "r"(cnt) : "memory"); }
__device__ __forceinline__ void mbar_arrive(uint32_t a) { asm volatile("mbarrier.arrive.shared.b64 _, [%0];" :: "r"(a) : "memory"); }
__device__ __forceinline__ void mbar_expect(uint32_t a, uint32_t bytes) { asm volatile("mbarrier.arrive.expect_tx.shared.b64 _, [%0], %1;" :: "r"(a), "r"(bytes) : "memory"); }
__device__ __forceinline__ void mbar_wait(uint32_t a, uint32_t parity) {
    uint32_t ok = 0;
#pragma unroll 1
    for (int it = 0; it < SPIN_LIMIT && !ok; ++it)
        asm volatile("{\n.reg .pred p;\nmbarrier.try_wait.parity.shared.b64 p, [%1], %2;\nselp.u32 %0, 1, 0, p;\n}"
                     : "=r"(ok) : "r"(a), "r"(parity) : "memory");
}
__device__ __forceinline__ bool elect() { uint32_t r; asm volatile("{\n.reg .pred p;\nelect.sync _|p, 0xffffffff;\nselp.u32 %0, 1, 0, p;\n}" : "=r"(r) :: "memory"); return r; }
__device__ __forceinline__ void warp_arrive(uint32_t a) {
    asm volatile("{\n.reg .pred p;\nelect.sync _|p, 0xffffffff;\n@p mbarrier.arrive.shared.b64 _, [%0];\n}" :: "r"(a) : "memory");
}
__device__ __forceinline__ void bar_sync(int id, int n)   { __syncwarp(); asm volatile("bar.sync %0, %1;"   :: "r"(id), "r"(n) : "memory"); }
__device__ __forceinline__ void bar_arrive(int id, int n) { __syncwarp(); asm volatile("bar.arrive %0, %1;" :: "r"(id), "r"(n) : "memory"); }
__device__ __forceinline__ void fence_async_smem() { asm volatile("fence.proxy.async.shared::cta;" ::: "memory"); }
__device__ __forceinline__ void fence_async_gmem() { asm volatile("fence.proxy.async.global;" ::: "memory"); }
__device__ __forceinline__ void tma2d(uint32_t dst, const CUtensorMap* tm, int c0, int c1, uint32_t bar) {
    asm volatile("cp.async.bulk.tensor.2d.shared::cluster.global.mbarrier::complete_tx::bytes [%0], [%1, {%3, %4}], [%2];"
                 :: "r"(dst), "l"(tm), "r"(bar), "r"(c0), "r"(c1) : "memory");
}
__device__ __forceinline__ void tma3d(uint32_t dst, const CUtensorMap* tm, int row, uint32_t bar) {
    asm volatile("cp.async.bulk.tensor.3d.shared::cluster.global.mbarrier::complete_tx::bytes [%0], [%1, {%4, %3, %4}], [%2];"
                 :: "r"(dst), "l"(tm), "r"(bar), "r"(row), "r"(0) : "memory");
}
__device__ __forceinline__ void tma2d_store(const CUtensorMap* tm, uint32_t src, int c0, int c1) {
    asm volatile("cp.async.bulk.tensor.2d.global.shared::cta.bulk_group [%0, {%2, %3}], [%1];"
                 :: "l"(tm), "r"(src), "r"(c0), "r"(c1) : "memory");
}
__device__ __forceinline__ void tma2d_add(const CUtensorMap* tm, uint32_t src, int c0, int c1) {
    asm volatile("cp.reduce.async.bulk.tensor.2d.global.shared::cta.add.bulk_group [%0, {%2, %3}], [%1];"
                 :: "l"(tm), "r"(src), "r"(c0), "r"(c1) : "memory");
}
__device__ __forceinline__ void bulk_load(uint32_t dst, const void* src, uint32_t bytes, uint32_t bar) {
    asm volatile("cp.async.bulk.shared::cluster.global.mbarrier::complete_tx::bytes [%0], [%1], %2, [%3];"
                 :: "r"(dst), "l"(src), "r"(bytes), "r"(bar) : "memory");
}
__device__ __forceinline__ void bulk_store(void* dst, uint32_t src, uint32_t bytes) {
    asm volatile("cp.async.bulk.global.shared::cta.bulk_group [%0], [%1], %2;" :: "l"(dst), "r"(src), "r"(bytes) : "memory");
}
__device__ __forceinline__ uint32_t clk() { uint32_t c; asm volatile("mov.u32 %0, %%clock;" : "=r"(c) :: "memory"); return c; }
__device__ __forceinline__ void wait_clk(uint32_t t) { while ((int)(clk() - t) < 0) {} }
__device__ __forceinline__ void bulk_commit() { asm volatile("cp.async.bulk.commit_group;" ::: "memory"); }
template <int K> __device__ __forceinline__ void bulk_wait_read() { asm volatile("cp.async.bulk.wait_group.read %0;" :: "n"(K) : "memory"); }
__device__ __forceinline__ void prefetch_map(const CUtensorMap* tm) { asm volatile("prefetch.tensormap [%0];" :: "l"(tm) : "memory"); }
__device__ __forceinline__ uint4 lds128(uint32_t a) { uint4 v; asm volatile("ld.shared.v4.u32 {%0,%1,%2,%3}, [%4];" : "=r"(v.x), "=r"(v.y), "=r"(v.z), "=r"(v.w) : "r"(a) : "memory"); return v; }
__device__ __forceinline__ void sts128(uint32_t a, uint4 v) { asm volatile("st.shared.v4.u32 [%0], {%1,%2,%3,%4};" :: "r"(a), "r"(v.x), "r"(v.y), "r"(v.z), "r"(v.w) : "memory"); }
__device__ __forceinline__ float4 lds128f(uint32_t a) { const uint4 v = lds128(a); return make_float4(__uint_as_float(v.x), __uint_as_float(v.y), __uint_as_float(v.z), __uint_as_float(v.w)); }
__device__ __forceinline__ void sts64(uint32_t a, uint32_t x, uint32_t y) { asm volatile("st.shared.v2.u32 [%0], {%1, %2};" :: "r"(a), "r"(x), "r"(y) : "memory"); }
__device__ __forceinline__ uint32_t lds32(uint32_t a) { uint32_t v; asm volatile("ld.shared.u32 %0, [%1];" : "=r"(v) : "r"(a) : "memory"); return v; }
__device__ __forceinline__ void sts32(uint32_t a, uint32_t v) { asm volatile("st.shared.u32 [%0], %1;" :: "r"(a), "r"(v) : "memory"); }
__device__ __forceinline__ void sts16(uint32_t a, uint32_t v) { asm volatile("st.shared.u16 [%0], %1;" :: "r"(a), "h"((unsigned short)v) : "memory"); }
__device__ __forceinline__ uint32_t atoms_add(uint32_t a, uint32_t x) { uint32_t v; asm volatile("atom.shared.add.u32 %0, [%1], %2;" : "=r"(v) : "r"(a), "r"(x) : "memory"); return v; }
__device__ __forceinline__ uint32_t ld_relaxed(const uint32_t* p) { uint32_t v; asm volatile("ld.relaxed.gpu.global.u32 %0, [%1];" : "=r"(v) : "l"(p) : "memory"); return v; }
__device__ __forceinline__ uint4 ld_relaxed4(const uint4* p) { uint4 v; asm volatile("ld.relaxed.gpu.global.L1::no_allocate.v4.u32 {%0,%1,%2,%3}, [%4];" : "=r"(v.x), "=r"(v.y), "=r"(v.z), "=r"(v.w) : "l"(p) : "memory"); return v; }
__device__ __forceinline__ uint32_t ld_acquire(const uint32_t* p) { uint32_t v; asm volatile("ld.acquire.gpu.global.u32 %0, [%1];" : "=r"(v) : "l"(p) : "memory"); return v; }
__device__ __forceinline__ void st_relaxed(uint32_t* p, uint32_t v) { asm volatile("st.relaxed.gpu.global.u32 [%0], %1;" :: "l"(p), "r"(v) : "memory"); }
__device__ __forceinline__ void red_relaxed(uint32_t* p) { asm volatile("red.relaxed.gpu.global.add.u32 [%0], 1;" :: "l"(p) : "memory"); }
__device__ __forceinline__ uint32_t list_tag(uint32_t epoch) { return (epoch % 3u + 1u) * 0x40004000u; }
__device__ __forceinline__ void red_release(uint32_t* p) { asm volatile("red.release.gpu.global.add.u32 [%0], 1;" :: "l"(p) : "memory"); }
__device__ __forceinline__ void wait_count(const uint32_t* p, uint32_t target) {
#pragma unroll 1
    for (int it = 0; it < SPIN_LIMIT; ++it)
        if ((int)(ld_acquire(p) - target) >= 0) break;
}
__device__ __forceinline__ uint4 ldg_in(const void* p) { uint4 v; asm volatile("ld.global.nc.L1::no_allocate.v4.u32 {%0,%1,%2,%3}, [%4];" : "=r"(v.x), "=r"(v.y), "=r"(v.z), "=r"(v.w) : "l"(p)); return v; }
__device__ __forceinline__ uint4 ldg_sc(const void* p) { uint4 v; asm volatile("ld.global.L1::no_allocate.v4.u32 {%0,%1,%2,%3}, [%4];" : "=r"(v.x), "=r"(v.y), "=r"(v.z), "=r"(v.w) : "l"(p) : "memory"); return v; }
__device__ __forceinline__ void red_row(uint4* p, uint4 v) { asm volatile("red.relaxed.gpu.global.add.noftz.v4.bf16x2 [%0], {%1,%2,%3,%4};" :: "l"(p), "r"(v.x), "r"(v.y), "r"(v.z), "r"(v.w) : "memory"); }
__device__ __forceinline__ uint32_t pack_bf16(float lo, float hi) { uint32_t r; asm("cvt.rn.bf16x2.f32 %0, %1, %2;" : "=r"(r) : "f"(hi), "f"(lo)); return r; }
__device__ __forceinline__ float blo(uint32_t v) { return __uint_as_float(v << 16); }
__device__ __forceinline__ float bhi(uint32_t v) { return __uint_as_float(v & 0xffff0000u); }
__device__ __forceinline__ const char* row_ptr(const char* base, uint32_t row) {
    uint64_t r; asm("mad.wide.u32 %0, %1, 512, %2;" : "=l"(r) : "r"(row), "l"((uint64_t)base)); return (const char*)r;
}

constexpr uint32_t DESC_HI = 64u | (1u << 30);
__device__ __forceinline__ uint32_t desc_lo(uint32_t addr) { return ((addr & 0x3FFFF) >> 4) | (1u << 16); }
__device__ __forceinline__ void wg_fence()  { asm volatile("wgmma.fence.sync.aligned;" ::: "memory"); }
__device__ __forceinline__ void wg_commit() { asm volatile("wgmma.commit_group.sync.aligned;" ::: "memory"); }
template <int K> __device__ __forceinline__ void wg_wait() { asm volatile("wgmma.wait_group.sync.aligned %0;" :: "n"(K) : "memory"); }
#define GK_ACC(c) c(d[0]), c(d[1]), c(d[2]), c(d[3]), c(d[4]), c(d[5]), c(d[6]), c(d[7]), c(d[8]), c(d[9]), \
    c(d[10]), c(d[11]), c(d[12]), c(d[13]), c(d[14]), c(d[15]), c(d[16]), c(d[17]), c(d[18]), c(d[19]), \
    c(d[20]), c(d[21]), c(d[22]), c(d[23]), c(d[24]), c(d[25]), c(d[26]), c(d[27]), c(d[28]), c(d[29]), \
    c(d[30]), c(d[31]), c(d[32]), c(d[33]), c(d[34]), c(d[35]), c(d[36]), c(d[37]), c(d[38]), c(d[39])
#define GK_WGMMA(P) "{\n.reg .pred p;\n.reg .b64 da, db;\nsetp.ne.b32 p, " P ", 0;\nmov.b64 da, {%40, %42};\nmov.b64 db, {%41, %42};\n" \
    "wgmma.mma_async.sync.aligned.m64n80k16.f32.bf16.bf16 " \
    "{%0,%1,%2,%3,%4,%5,%6,%7,%8,%9,%10,%11,%12,%13,%14,%15,%16,%17,%18,%19," \
    "%20,%21,%22,%23,%24,%25,%26,%27,%28,%29,%30,%31,%32,%33,%34,%35,%36,%37,%38,%39}, da, db, p, 1, 1, 1, 0;\n}\n"
template <bool FIRST>
__device__ __forceinline__ void wgmma80(float (&d)[40], uint32_t alo, uint32_t blo_) {
    if (FIRST) asm volatile(GK_WGMMA("0") : GK_ACC("=f") : "r"(alo), "r"(blo_), "r"(DESC_HI));
    else       asm volatile(GK_WGMMA("1") : GK_ACC("+f") : "r"(alo), "r"(blo_), "r"(DESC_HI));
}
template <int KQ>
__device__ __forceinline__ void gemm_quarter(float (&d)[40], uint32_t unit, uint32_t tile, uint32_t bar, uint32_t parity, uint32_t rel = 0) {
    mbar_wait(bar + KQ * 8, parity);
    __syncwarp();
    const uint32_t a = desc_lo(unit), b = desc_lo(tile) + ((KQ * KB) >> 4);
    wg_fence();
    wgmma80<KQ == 0>(d, a, b);
    if (KQ) { wg_commit(); wg_wait<1>(); warp_arrive(rel); }
    wgmma80<false>(d, a + 128, b + 2);
    wgmma80<false>(d, a + 256, b + 4);
    wgmma80<false>(d, a + 384, b + 6);
    wg_commit();
}
__device__ __forceinline__ void stsm4t(uint32_t a, uint32_t r0, uint32_t r1, uint32_t r2, uint32_t r3) {
    asm volatile("stmatrix.sync.aligned.m8n8.x4.trans.shared.b16 [%0], {%1,%2,%3,%4};" :: "r"(a), "r"(r0), "r"(r1), "r"(r2), "r"(r3) : "memory");
}
__device__ __forceinline__ void stsm4(uint32_t a, uint32_t r0, uint32_t r1, uint32_t r2, uint32_t r3) {
    asm volatile("stmatrix.sync.aligned.m8n8.x4.shared.b16 [%0], {%1,%2,%3,%4};" :: "r"(a), "r"(r0), "r"(r1), "r"(r2), "r"(r3) : "memory");
}
__device__ __forceinline__ uint4 ldsm4(uint32_t a) {
    uint4 v; asm volatile("ldmatrix.sync.aligned.m8n8.x4.shared.b16 {%0,%1,%2,%3}, [%4];" : "=r"(v.x), "=r"(v.y), "=r"(v.z), "=r"(v.w) : "r"(a) : "memory"); return v;
}
__device__ __forceinline__ void mma16816(float (&c)[4], uint32_t a0, uint32_t a1, uint32_t a2, uint32_t a3, uint32_t b0, uint32_t b1) {
    asm volatile("mma.sync.aligned.m16n8k16.row.col.f32.bf16.bf16.f32 {%0,%1,%2,%3}, {%4,%5,%6,%7}, {%8,%9}, {%0,%1,%2,%3};"
        : "+f"(c[0]), "+f"(c[1]), "+f"(c[2]), "+f"(c[3]) : "r"(a0), "r"(a1), "r"(a2), "r"(a3), "r"(b0), "r"(b1));
}
__device__ __forceinline__ void pack_acc(uint32_t (&h)[20], const float (&d)[40]) {
#pragma unroll
    for (int i = 0; i < 20; ++i) h[i] = pack_bf16(d[2 * i], d[2 * i + 1]);
}
__device__ __forceinline__ void store_tile(const uint32_t (&h)[20], uint32_t tile, int mt, int w4, int lane) {
    const int r = lane & 7;
    const uint32_t base = tile + mt * KB + (((lane >> 4) * 8 + r) * 128) + (((2 * w4 + ((lane >> 3) & 1)) ^ r) << 4);
#pragma unroll
    for (int i = 0; i < 5; ++i) stsm4t(base + i * 2048, h[4 * i], h[4 * i + 1], h[4 * i + 2], h[4 * i + 3]);
}
__device__ __forceinline__ void fma8(float (&a)[8], float w, const uint4& v) {
    a[0] = fmaf(w, blo(v.x), a[0]); a[1] = fmaf(w, bhi(v.x), a[1]);
    a[2] = fmaf(w, blo(v.y), a[2]); a[3] = fmaf(w, bhi(v.y), a[3]);
    a[4] = fmaf(w, blo(v.z), a[4]); a[5] = fmaf(w, bhi(v.z), a[5]);
    a[6] = fmaf(w, blo(v.w), a[6]); a[7] = fmaf(w, bhi(v.w), a[7]);
}
__device__ __forceinline__ float dot8(const float (&q)[8], const uint4& v) {
    float s = q[0] * blo(v.x);
    s = fmaf(q[1], bhi(v.x), s); s = fmaf(q[2], blo(v.y), s); s = fmaf(q[3], bhi(v.y), s);
    s = fmaf(q[4], blo(v.z), s); s = fmaf(q[5], bhi(v.z), s); s = fmaf(q[6], blo(v.w), s); s = fmaf(q[7], bhi(v.w), s);
    return s;
}
__device__ __forceinline__ uint4 pack8(const float (&a)[8], float s) {
    return make_uint4(pack_bf16(a[0] * s, a[1] * s), pack_bf16(a[2] * s, a[3] * s), pack_bf16(a[4] * s, a[5] * s), pack_bf16(a[6] * s, a[7] * s));
}
__device__ __forceinline__ uint32_t hmul2(uint32_t a, uint32_t b) { uint32_t d; asm("mul.rn.bf16x2 %0, %1, %2;" : "=r"(d) : "r"(a), "r"(b)); return d; }
__device__ __forceinline__ uint32_t tile_chunk(uint32_t tile, int r, int c) {
    return tile + (c >> 3) * KB + r * 128 + (((c & 7) ^ (r & 7)) << 4);
}
__device__ __forceinline__ uint32_t wsum4(const uint32_t (&a)[4], uint32_t r0, uint32_t r1, uint32_t r2, uint32_t r3) {
    uint32_t z;
    asm("{\n.reg .b32 t;\nmul.rn.bf16x2 t, %1, %5;\nfma.rn.bf16x2 t, %2, %6, t;\nfma.rn.bf16x2 t, %3, %7, t;\nfma.rn.bf16x2 %0, %4, %8, t;\n}"
        : "=r"(z) : "r"(a[0]), "r"(a[1]), "r"(a[2]), "r"(a[3]), "r"(r0), "r"(r1), "r"(r2), "r"(r3));
    return z;
}
__device__ __forceinline__ void softmax4(const float (&s)[4], const float (&u)[4], int lane, uint32_t (&a)[4]) {
    const bool b = lane & 4, c = lane & 8;
    const float k0 = (b ? u[1] : s[0]) + __shfl_xor_sync(0xffffffffu, b ? s[1] : u[0], 4);
    const float k1 = (b ? u[3] : s[2]) + __shfl_xor_sync(0xffffffffu, b ? s[3] : u[2], 4);
    const float e = (c ? k1 : k0) + __shfl_xor_sync(0xffffffffu, c ? k0 : k1, 9);
    float pe;
    asm("ex2.approx.ftz.f32 %0, %1;" : "=f"(pe) : "f"(e * (0.0625f * 1.4426950408889634f)));
    const int l0 = (lane >> 4) * 18;
    const float p0 = __shfl_sync(0xffffffffu, pe, l0), p1 = __shfl_sync(0xffffffffu, pe, l0 + 9);
    const float p2 = __shfl_sync(0xffffffffu, pe, l0 + 4), p3 = __shfl_sync(0xffffffffu, pe, l0 + 13);
    float inv;
    asm("rcp.approx.ftz.f32 %0, %1;" : "=f"(inv) : "f"(((p0 + p1) + (p2 + p3)) + 1e-9f));
    a[0] = pack_bf16(p0 * inv, p0 * inv); a[1] = pack_bf16(p1 * inv, p1 * inv);
    a[2] = pack_bf16(p2 * inv, p2 * inv); a[3] = pack_bf16(p3 * inv, p3 * inv);
}
__device__ __forceinline__ void attention_chunks(const uint4 (&r)[4][2], uint32_t tile, int node, int lane) {
    const uint32_t qa = tile_chunk(tile, node + (lane >> 4), lane & 15);
    const uint4 q0 = lds128(qa), q1 = lds128(qa + 2 * KB);
    float s[4] = {0.f, 0.f, 0.f, 0.f}, u[4] = {0.f, 0.f, 0.f, 0.f};
    mma16816(s, r[0][0].x, r[1][0].x, r[0][0].y, r[1][0].y, q0.x, q0.y); mma16816(u, r[2][0].x, r[3][0].x, r[2][0].y, r[3][0].y, q0.x, q0.y);
    mma16816(s, r[0][0].z, r[1][0].z, r[0][0].w, r[1][0].w, q0.z, q0.w); mma16816(u, r[2][0].z, r[3][0].z, r[2][0].w, r[3][0].w, q0.z, q0.w);
    mma16816(s, r[0][1].x, r[1][1].x, r[0][1].y, r[1][1].y, q1.x, q1.y); mma16816(u, r[2][1].x, r[3][1].x, r[2][1].y, r[3][1].y, q1.x, q1.y);
    mma16816(s, r[0][1].z, r[1][1].z, r[0][1].w, r[1][1].w, q1.z, q1.w); mma16816(u, r[2][1].z, r[3][1].z, r[2][1].w, r[3][1].w, q1.z, q1.w);
    uint32_t a[4];
    softmax4(s, u, lane, a);
#pragma unroll
    for (int h = 0; h < 2; ++h)
        sts128(qa + h * 2 * KB, make_uint4(wsum4(a, r[0][h].x, r[1][h].x, r[2][h].x, r[3][h].x), wsum4(a, r[0][h].y, r[1][h].y, r[2][h].y, r[3][h].y),
                                           wsum4(a, r[0][h].z, r[1][h].z, r[2][h].z, r[3][h].z), wsum4(a, r[0][h].w, r[1][h].w, r[2][h].w, r[3][h].w)));
}
__device__ __forceinline__ void attention_frags(const uint4 (&r)[2][4], uint32_t tile, int node, int lane) {
    const int nd = node + ((lane >> 2) & 1);
    const uint32_t qa = tile + (lane >> 4) * KB + nd * 128 + (((lane ^ (lane >> 1 & 4) ^ nd) & 7) << 4);
    const uint4 q0 = ldsm4(qa), q1 = ldsm4(qa + 2 * KB);
    float s[4] = {0.f, 0.f, 0.f, 0.f}, u[4] = {0.f, 0.f, 0.f, 0.f};
    mma16816(s, r[0][0].x, r[0][0].y, r[0][0].z, r[0][0].w, q0.x, q0.y); mma16816(u, r[1][0].x, r[1][0].y, r[1][0].z, r[1][0].w, q0.x, q0.y);
    mma16816(s, r[0][1].x, r[0][1].y, r[0][1].z, r[0][1].w, q0.z, q0.w); mma16816(u, r[1][1].x, r[1][1].y, r[1][1].z, r[1][1].w, q0.z, q0.w);
    mma16816(s, r[0][2].x, r[0][2].y, r[0][2].z, r[0][2].w, q1.x, q1.y); mma16816(u, r[1][2].x, r[1][2].y, r[1][2].z, r[1][2].w, q1.x, q1.y);
    mma16816(s, r[0][3].x, r[0][3].y, r[0][3].z, r[0][3].w, q1.z, q1.w); mma16816(u, r[1][3].x, r[1][3].y, r[1][3].z, r[1][3].w, q1.z, q1.w);
    uint32_t a[4];
    softmax4(s, u, lane, a);
#pragma unroll
    for (int h = 0; h < 2; ++h)
        stsm4(qa + h * 2 * KB, wsum4(a, r[0][2 * h].x, r[0][2 * h].y, r[1][2 * h].x, r[1][2 * h].y), wsum4(a, r[0][2 * h].z, r[0][2 * h].w, r[1][2 * h].z, r[1][2 * h].w),
              wsum4(a, r[0][2 * h + 1].x, r[0][2 * h + 1].y, r[1][2 * h + 1].x, r[1][2 * h + 1].y), wsum4(a, r[0][2 * h + 1].z, r[0][2 * h + 1].w, r[1][2 * h + 1].z, r[1][2 * h + 1].w));
}
__device__ __noinline__ void attention_generic(const Params& p, uint32_t tile, int nl, int node, int lane) {
    const uint32_t qa = tile_chunk(tile, nl, lane);
    const uint4 qv = lds128(qa);
    const float q[8] = {blo(qv.x), bhi(qv.x), blo(qv.y), bhi(qv.y), blo(qv.z), bhi(qv.z), blo(qv.w), bhi(qv.w)};
    float z[8] = {0.f, 0.f, 0.f, 0.f, 0.f, 0.f, 0.f, 0.f};
    float den = 0.f;
#pragma unroll 1
    for (int e = 0; e < p.Ee; e += 32) {
        const bool m = (e + lane < p.Ee) && (__ldg(p.edst + e + lane) == node);
        const int sv = m ? __ldg(p.esrc + e + lane) : 0;
        uint32_t bal = __ballot_sync(0xffffffffu, m);
        while (bal) {
            const int l = __ffs(bal) - 1; bal &= bal - 1;
            const uint4 v = ldg_in(row_ptr(p.x + lane * 16, __shfl_sync(0xffffffffu, sv, l)));
            float c = dot8(q, v);
#pragma unroll
            for (int o = 16; o; o >>= 1) c += __shfl_xor_sync(0xffffffffu, c, o);
            const float pe = expf(c * 0.0625f);
            den += pe;
            fma8(z, pe, v);
        }
    }
    sts128(qa, pack8(z, 1.f / (den + 1e-9f)));
}
__device__ __noinline__ void local_generic(const Params& p, int node0, int w, int lane) {
    float a0[8], a1[8], a2[8], a3[8];
#pragma unroll
    for (int k = 0; k < 8; ++k) { a0[k] = 0.f; a1[k] = 0.f; a2[k] = 0.f; a3[k] = 0.f; }
#pragma unroll 1
    for (int e = 0; e < p.E; e += 32) {
        const int dl = (e + lane < p.E) ? __ldg(p.dst + e + lane) - node0 - w : -1;
        const int k = dl == 0 ? 0 : dl == AW ? 1 : dl == 2 * AW ? 2 : (dl == 3 * AW && w + 3 * AW < NPC) ? 3 : -1;
        const int sv = k >= 0 ? __ldg(p.src + e + lane) : 0;
        uint32_t bal = __ballot_sync(0xffffffffu, k >= 0);
        while (bal) {
            const int l = __ffs(bal) - 1; bal &= bal - 1;
            const int s = __shfl_sync(0xffffffffu, sv, l), kk = __shfl_sync(0xffffffffu, k, l);
            const uint4 v = ldg_sc(p.H + lane * N + s);
            if (kk & 2) { if (kk & 1) fma8(a3, 1.f, v); else fma8(a2, 1.f, v); }
            else        { if (kk & 1) fma8(a1, 1.f, v); else fma8(a0, 1.f, v); }
        }
    }
    const int n = node0 + w;
    red_row(p.out + n * 32 + lane, pack8(a0, __bfloat162float(p.dis[n])));
    red_row(p.out + (n + AW) * 32 + lane, pack8(a1, __bfloat162float(p.dis[n + AW])));
    red_row(p.out + (n + 2 * AW) * 32 + lane, pack8(a2, __bfloat162float(p.dis[n + 2 * AW])));
    if (w + 3 * AW < NPC) red_row(p.out + (n + 3 * AW) * 32 + lane, pack8(a3, __bfloat162float(p.dis[n + 3 * AW])));
}
__device__ __forceinline__ uint32_t hadd2(uint32_t a, uint32_t b) { uint32_t d; asm("add.rn.bf16x2 %0, %1, %2;" : "=r"(d) : "r"(a), "r"(b)); return d; }
__device__ __forceinline__ float plo(uint32_t v) { uint32_t d; asm("prmt.b32 %0, %1, 0, 0x1044;" : "=r"(d) : "r"(v)); return __uint_as_float(d); }
template <int HI, int NR>
__device__ __forceinline__ uint32_t agg_sum(uint32_t w, uint32_t base) {
    uint32_t a, r0, r1, r2, r3;
    if (HI) asm("dp2a.hi.u32.u32 %0, %1, %2, %3;" : "=r"(a) : "r"(w), "r"(0x10000010u), "r"(base));
    else    asm("dp2a.lo.u32.u32 %0, %1, %2, %3;" : "=r"(a) : "r"(w), "r"(0x10000010u), "r"(base));
    if (NR == 2) {
        asm volatile("ldmatrix.sync.aligned.m8n8.x2.shared.b16 {%0,%1}, [%2];" : "=r"(r0), "=r"(r1) : "r"(a));
        return hadd2(r0, r1);
    }
    asm volatile("ldmatrix.sync.aligned.m8n8.x4.shared.b16 {%0,%1,%2,%3}, [%4];" : "=r"(r0), "=r"(r1), "=r"(r2), "=r"(r3) : "r"(a));
    return hadd2(hadd2(r0, r1), hadd2(r2, r3));
}
struct Unit { uint4 a, b; };
__device__ __forceinline__ uint32_t unit_stale(const Unit& x, uint32_t lt) {
    return ((x.a.x ^ lt) | (x.b.x ^ lt)) & 0xc000u;
}
__device__ __forceinline__ uint32_t agg_tail(float lo, float hi, uint32_t s, const uint4& w, uint32_t base, uint32_t b5, uint32_t b6) {
    if (b5 > 0xffffu) {
        s = hadd2(s, agg_sum<1, 4>(w.z, base));
        if (b6) {
            const uint32_t u = b6 > 0xffffu ? agg_sum<0, 4>(w.w, base) : agg_sum<0, 2>(w.w, base);
            lo += plo(u); hi += bhi(u);
        }
    } else if (b5) s = hadd2(s, agg_sum<1, 2>(w.z, base));
    const float f = bhi(w.w);
    return pack_bf16((lo + plo(s)) * f, (hi + bhi(s)) * f);
}
__device__ __forceinline__ void agg_unit(const Unit& x, uint32_t base, uint32_t stg, uint32_t lt) {
    const uint32_t s0 = hadd2(agg_sum<0, 4>(x.a.x, base), agg_sum<1, 4>(x.a.x, base)), u0 = hadd2(agg_sum<0, 4>(x.b.x, base), agg_sum<1, 4>(x.b.x, base));
    const uint32_t s1 = hadd2(agg_sum<0, 4>(x.a.y, base), agg_sum<1, 4>(x.a.y, base)), u1 = hadd2(agg_sum<0, 4>(x.b.y, base), agg_sum<1, 4>(x.b.y, base));
    const uint32_t s2 = agg_sum<0, 4>(x.a.z, base), u2 = agg_sum<0, 4>(x.b.z, base);
    const uint32_t a5 = __ballot_sync(0xffffffffu, x.a.z > (lt | 0xffffu)), a6 = __ballot_sync(0xffffffffu, x.a.w & 0x3fffu);
    const uint32_t b5 = __ballot_sync(0xffffffffu, x.b.z > (lt | 0xffffu)), b6 = __ballot_sync(0xffffffffu, x.b.w & 0x3fffu);
    const uint32_t oa = agg_tail(plo(s0) + plo(s1), bhi(s0) + bhi(s1), s2, x.a, base, a5, a6);
    const uint32_t ob = agg_tail(plo(u0) + plo(u1), bhi(u0) + bhi(u1), u2, x.b, base, b5, b6);
    asm volatile("stmatrix.sync.aligned.m8n8.x2.shared.b16 [%0], {%1,%2};" :: "r"(stg), "r"(oa), "r"(ob) : "memory");
}

__global__ void __launch_bounds__(NTHR, 1)
fused_kernel(const __grid_constant__ Params p,
             const __grid_constant__ CUtensorMap tmX, const __grid_constant__ CUtensorMap tmWl,
             const __grid_constant__ CUtensorMap tmM, const __grid_constant__ CUtensorMap tmWv,
             const __grid_constant__ CUtensorMap tmR, const __grid_constant__ CUtensorMap tmO,
             const __grid_constant__ CUtensorMap tmG, const __grid_constant__ CUtensorMap tmQ,
             const __grid_constant__ CUtensorMap tmK, const __grid_constant__ CUtensorMap tmV3)
{
    extern __shared__ __align__(1024) unsigned char smem[];
    constexpr uint32_t sb = 1024;
    const int tid = threadIdx.x, lane = tid & 31;
    const int warp = __shfl_sync(0xffffffffu, tid >> 5, 0);
    const int cta = blockIdx.x;
    const int node0 = cta * NPC;
    const bool rowcta = cta < RCTA;
    const int slice = cta >> 2, quarter = cta & 3;
    const int nlast = 12 + (quarter == 3);
    const int i0 = (cta >> 3) * 16, j0 = (cta & 7) * 32;
    constexpr uint32_t bars = sb + SM_MISC, sS = sb + SM_S, sT = sb + SM_T;

    const bool stage = rowcta && p.edst4;
    auto slow_cta = [&]() { uint32_t a, b; asm volatile("ld.shared.v2.u32 {%0, %1}, [%2];" : "=r"(a), "=r"(b) : "r"(bars + MI_SLOW) : "memory"); return a || b > OVCAP; };
    auto publish = [&](int set) {
        const uint4 dv = lds128(bars + MI_DIS + set * 16);
        uint4 v = lds128(sb + X_IMG + set * 512 + lane * 16);
        const uint4 z = lds128(sb + X_DEF + set * 64 + (lane & 3) * 16);
        if ((lane & 3) == 3) { v.x = __byte_perm(v.x, v.y, 0x5410); v.y = v.w; }
        v.x = __vmaxu2(v.x, z.x); v.y = __vmaxu2(v.y, z.y); v.z = __vmaxu2(v.z, z.z); v.w = __vmaxu2(v.w, z.w);
        if (slow_cta()) v = make_uint4(0, 0, 0, 0);
        const uint32_t lt = list_tag(lds32(bars + MI_EPOCH));
        v.x |= lt; v.y |= lt; v.z |= lt; v.w |= lt;
        if ((lane & 3) == 3) { const uint32_t sel = lane & 16 ? 0x7632 : 0x5410; v.z = __byte_perm(dv.x, dv.y, sel); v.w = __byte_perm(dv.z, dv.w, sel); }
        uint32_t* ip = (uint32_t*)p.idx + (cta * 10 + set) * 128 + lane;
        st_relaxed(ip, __byte_perm(v.x, v.z, 0x5410));      st_relaxed(ip + 32, __byte_perm(v.x, v.z, 0x7632));
        st_relaxed(ip + 64, __byte_perm(v.y, v.w, 0x5410)); st_relaxed(ip + 96, __byte_perm(v.y, v.w, 0x7632));
    };

    if (warp >= AW) {
        const int pw = warp - AW;
        auto init = [&](int b0, int b1, int c) {
#pragma unroll
            for (int b = b0; b < b1; b += 8) mbar_init(bars + b, c);
        };
        uint4 pe = make_uint4(0, 0, 0, 0);
        if (pw == 0) {
            if (elect()) {
                PROF(0);
                prefetch_map(&tmQ); prefetch_map(&tmK); prefetch_map(&tmX); prefetch_map(&tmWl);
                init(B_K, B_A, 1);
                asm volatile("fence.mbarrier_init.release.cluster;" ::: "memory");
                mbar_expect(bars + B_QK, 3 * UNIT);
                tma3d(sS + A3 * UNIT, &tmQ, i0, bars + B_QK);
                tma3d(sS + (A3 + 1) * UNIT, &tmK, j0, bars + B_QK);
            }
        } else {
            if (elect()) {
                if (pw & 2) {
                    if (pw & 1) { init(B_GO, B_Z, 1); init(B_RND, B_RND + 96, 12); mbar_init(bars + B_RND + 96, nlast); }
                    else        { init(B_F, B_GO, GW); init(B_FA, B_SENT, 8); mbar_init(bars + B_SENT, LW + 4); }
                } else          { init(B_A, B_F, 4); mbar_init(bars + B_S, 6); mbar_init(bars + B_VE, GW); mbar_init(bars + B_Z, AW); init(B_HV, B_RV + 8, 1); }
                asm volatile("fence.mbarrier_init.release.cluster;" ::: "memory");
            }
        }
        bar_arrive(4, LT + 128);
        bar_arrive(0, GT + 128);
        if (pw == 0 && rowcta && elect()) {
#pragma unroll
            for (int kq = 0; kq < 4; ++kq) mbar_expect(bars + B_K + kq * 8, KB + 4 * UNIT);
#pragma unroll
            for (int i = 7; i >= 0; --i) {
                const int kq = (XORD >> (4 * i)) & 3;
                if ((XORD >> (4 * i)) & 4) tma3d(sS + (kq == 3 ? A4 : 4 * kq) * UNIT, &tmWl, kq * 64, bars + B_K + kq * 8);
                else tma2d(sT + kq * KB, &tmX, kq * 64, node0, bars + B_K + kq * 8);
            }
            PROF(3);
            prefetch_map(&tmM); prefetch_map(&tmG); prefetch_map(&tmWv); prefetch_map(&tmV3); prefetch_map(&tmR);
        }
        if (pw >= 2 ? stage : pw && rowcta && lane < 10) pe = ldg_in(pw >= 2 ? (const char*)(p.esrc + (node0 + 32 * (pw - 2) + lane) * 4) : (const char*)(p.dis + node0 + lane * 8));
        auto load_units = [&](const CUtensorMap* tm, int kq, int slot) {
            if (elect()) { mbar_expect(bars + B_K + kq * 8, 4 * UNIT); tma3d(sS + slot * UNIT, tm, kq * 64, bars + B_K + kq * 8); }
        };
        const int v0 = pw ? pw - 2 : 2;
        auto tile_rows = [&](uint2 (&e)[6], int c) {
#pragma unroll
            for (int n = 0; n < 6; ++n) {
                const int v = min(v0 + 3 * n, 15);
                asm volatile("ld.shared.v2.u32 {%0, %1}, [%2];" : "=r"(e[n].x), "=r"(e[n].y) : "r"(bars + MI_ES + ((v >> 2) * 16 + c * 4 + (v & 3)) * 8) : "memory");
            }
        };
        auto stage_tiles = [&](const uint2 (&e)[6], int c) {
            mbar_wait(bars + (c ? B_F + 32 + c * 8 : B_CGO), 0);
            if (elect()) {
#pragma unroll
                for (int n = 0; n < 6; ++n) {
                    const int v = v0 + 3 * n;
                    if (n < 5 || v < 16) {
                        const uint32_t dst = sS + (A_TILES >> (8 * c) & 255) * UNIT + v * 2048, bar = bars + B_A + ((v & 12) + c) * 8;
                        mbar_expect(bar, 2048);
                        tma2d(dst, &tmG, 0, e[n].x & 0xffffu, bar);        tma2d(dst + 512, &tmG, 0, e[n].x >> 16, bar);
                        tma2d(dst + 1024, &tmG, 0, e[n].y & 0xffffu, bar); tma2d(dst + 1536, &tmG, 0, e[n].y >> 16, bar);
                    }
                }
            }
            if (pw == 2 && lane == 0) PROF(45 + c);
        };
        if (pw >= 2) asm volatile("st.shared.v2.u32 [%0], {%1, %2};" :: "r"(bars + MI_ES + ((pw - 2) * 32 + lane) * 8), "r"(pe.x | pe.y << 16), "r"(pe.z | pe.w << 16) : "memory");
        else if (pw == 1 && lane < 10) sts128(bars + MI_DIS + lane * 16, pe);
        {
            bar_sync(1, GT + 128);
            const int v = tid - AW * 32;
            const uint32_t rp = sb + SM_X + ((v >> 3) * 32 + (((v & 7) * 4 + (v & 24)) & 31)) * 4;
            const float4 v0 = lds128f(rp), v1 = lds128f(rp + 2048), v2 = lds128f(rp + 4096), v3 = lds128f(rp + 6144);
            p.M[(i0 + (v >> 3)) * 64 + (j0 >> 2) + (v & 7)] =
                make_uint2(pack_bf16((v0.x + v1.x) + (v2.x + v3.x), (v0.y + v1.y) + (v2.y + v3.y)),
                           pack_bf16((v0.z + v1.z) + (v2.z + v3.z), (v0.w + v1.w) + (v2.w + v3.w)));
            warp_arrive(bars + B_SENT);
        }
        if (pw != 1 && rowcta) {
            uint2 e[3][6];
#pragma unroll
            for (int c = 0; c < 3; ++c) tile_rows(e[c], c);
            mbar_wait(bars + B_EPO, 0);
            mbar_wait(bars + B_F, 0);
#pragma unroll 1
            for (int c = 0; c < 3; ++c) {
                if (pw == 0 && c == 0) {
                    mbar_wait(bars + B_CGO, 0);
                    wait_count(p.sync + SY_M, (lds32(bars + MI_EPOCH) + 1) * NCTA);
                    fence_async_gmem();
                    if (lane == 0) PROF(2);
                    load_units(&tmM, 0, A0);
                    if (lane == 0) PROF(39);
                    mbar_wait(bars + B_F + 8, 0);  load_units(&tmM, 1, A1);
                    mbar_wait(bars + B_F + 16, 0); load_units(&tmM, 2, A2);
                    warp_arrive(bars + B_MI);
                    if (lane == 0) PROF(40);
                }
                if (pw == 0 && c == 1) { mbar_wait(bars + B_F + 32, 0); load_units(&tmM, 3, A0); }
                if (stage) stage_tiles(e[0], c);
#pragma unroll
                for (int n = 0; n < 6; ++n) { e[0][n] = e[1][n]; e[1][n] = e[2][n]; }
            }
        }
        if (pw == 0) {
            if (rowcta) {
                mbar_wait(bars + B_FA, 0); mbar_wait(bars + B_FA + 8, 0); fence_async_smem();
                mbar_wait(bars + B_HR, 0);
                if (elect()) {
                    mbar_expect(bars + B_K, 4 * UNIT);     tma3d(sS + A3 * UNIT, &tmWv, 0, bars + B_K);
                    mbar_expect(bars + B_K + 8, 4 * UNIT); tma3d(sS + A1 * UNIT, &tmWv, 64, bars + B_K + 8);
                }
                mbar_wait(bars + B_FA + 16, 0); fence_async_smem();  load_units(&tmWv, 2, A2);
                mbar_wait(bars + B_XF, 0);      fence_async_smem();
                if (elect()) {
                    mbar_expect(bars + B_K + 24, 4 * UNIT);
#pragma unroll
                    for (int ks = 0; ks < 4; ++ks) tma3d(sS + (A5 + ks) * UNIT, &tmV3, 192 + ks * 16, bars + B_K + 24);
                }
                if (lane == 0) PROF(5);
            }
        } else if (pw == 1) {
            mbar_wait(bars + B_SENT, 0);
            if (elect()) { PROF(38); red_release(p.sync + SY_M); PROF(1); mbar_arrive(bars + B_CGO); }
            if (lane < 8) asm volatile("prefetch.global.L2 [%0];" :: "l"(p.wv + (cta * 8 + lane) * 128));
            mbar_wait(bars + B_EPO, 0);
            if (rowcta) {
                mbar_wait(bars + B_HS, 0);
                mbar_wait(bars + B_LF, 0);
                fence_async_smem();
                mbar_wait(bars + B_MI, 0);
                mbar_wait(bars + B_K, 1);
                uint32_t tn = clk();
#pragma unroll 1
                for (int s = 0; s < 32; s += 2) {
                    wait_clk(tn); tn += HPER;
                    if (elect()) {
                        bulk_store(p.H + s * N + node0, sS + A4 * UNIT + s * 1280, 1280);
                        bulk_store(p.H + (s + 1) * N + node0, sS + A4 * UNIT + s * 1280 + 1280, 1280);
                    }
                }
#pragma unroll 1
                for (int z = cta; z < ER * AW * 16; z += RCTA) {
                    wait_clk(tn); tn += HPER;
                    if (elect()) bulk_store(p.out + ((z & 3) * (UPQ * 16) + (z >> 2) * 4) * 32, sb + X_ZERO, 2048);
                }
                if (elect()) {
                    bulk_commit();
                    asm volatile("cp.async.bulk.wait_group 0;" ::: "memory");
                    PROF(43);
                    fence_async_gmem();
                    red_release(p.sync + SY_H);
                    mbar_arrive(bars + B_HR);
                    PROF(31);
                }
            }
            const uint32_t target = (lds32(bars + MI_EPOCH) + 1) * RCTA;
            if (rowcta) mbar_wait(bars + B_FA + 24, 0);
            if (lane < 8) sts128(sS + lane * 16, make_uint4(0, 0, 0, 0));
            fence_async_smem();
            wait_count(p.sync + SY_H, target);
            fence_async_gmem();
            if (lane == 0) PROF(6);
            const char* hs = (const char*)(p.H + slice * N) - 128;
            auto chunk = [&](int lo, int hi) { mbar_expect(bars + B_S, hi - lo); bulk_load(sS + lo, hs + lo, hi - lo, bars + B_S); };
            if (elect()) { chunk(A4 * UNIT, A5 * UNIT); chunk(128, 4 * UNIT); mbar_arrive(bars + B_HV); }
            if (rowcta) mbar_wait(bars + B_F + 64, 0);
            if (elect()) chunk(A3 * UNIT, (A3 + 4) * UNIT);
            if (rowcta) mbar_wait(bars + B_F + 72, 0);
            if (elect()) chunk(A1 * UNIT, (A1 + 4) * UNIT);
            if (rowcta) mbar_wait(bars + B_F + 80, 0);
            if (elect()) chunk(A2 * UNIT, (A2 + 4) * UNIT);
            if (rowcta) mbar_wait(bars + B_F + 88, 0);
            if (elect()) chunk(A5 * UNIT, SLICE_END);
            if (lane == 0) PROF(7);
        } else {
            mbar_wait(bars + B_EPO, 0);
            const uint32_t epoch1 = lds32(bars + MI_EPOCH) + 1;
            if (pw == 2) {
                if (rowcta) {
                    uint32_t early = 0;
#pragma unroll
                    for (int r = 0; r < 5; ++r) { const int u = cta * 5 + r; early |= (u - min(u / UPQ, 3) * UPQ < ER * AW) << r; }
                    auto put_r = [&](bool add) {
#pragma unroll 1
                        for (int r = 0; r < 5; ++r) {
                            const int u = cta * 5 + r;
                            if ((early >> r & 1) == add) {
                                if (elect()) {
#pragma unroll
                                    for (int kb = 0; kb < 4; ++kb) {
                                        if (add) tma2d_add(&tmR, sT + kb * KB + r * 2048, kb * 64, u * 16);
                                        else     tma2d_store(&tmR, sT + kb * KB + r * 2048, kb * 64, u * 16);
                                    }
                                }
                            }
                        }
                        bulk_commit();
                    };
                    mbar_wait(bars + B_R, 0);
                    fence_async_smem();
                    put_r(false);
                    if (elect()) {
                        asm volatile("cp.async.bulk.wait_group 0;" ::: "memory");
                        fence_async_gmem();
                        p.sync[SY_SLOW + cta] = slow_cta();
                        red_release(p.sync + SY_R);
                        PROF(22);
                    }
                    mbar_wait(bars + B_S, 0);
                    put_r(true);
                    bulk_wait_read<0>();
                    if (lane == 0) PROF(41);
                }
                warp_arrive(bars + B_TF);
                wait_count(p.sync + SY_R, epoch1 * RCTA);
                fence_async_gmem();
                warp_arrive(bars + B_RV);
                if (lane == 0) PROF(23);
            } else {
                if (s32(smem) != sb) __trap();
                if (lane == 0) prefetch_map(&tmO);
                mbar_wait(bars + B_XF, 0);
                if (elect()) red_relaxed(p.sync + SY_L);
                wait_count(p.sync + SY_L, epoch1 * NCTA);
                warp_arrive(bars + B_GO);
                if (lane == 0) PROF(42);
                if (cta == 0 && lane < 16) *(volatile uint32_t*)(p.sync + lane * 32) = epoch1;
#pragma unroll 1
                for (int i = 0; i < 13; ++i) {
                    if (i == 2 * ER) mbar_wait(bars + B_RV, 0);
                    mbar_wait(bars + B_RND + i * 8, 0);
                    fence_async_smem();
                    if (elect()) {
                        tma2d_add(&tmO, sb + SM_X + i * 3072, slice * 8, quarter * (UPQ * 16) + i * 192);
                        if (i == 12 && quarter == 3) tma2d_add(&tmO, sb + SM_X + 13 * 3072, slice * 8, 3 * (UPQ * 16) + 13 * 192);
                    }
                    if (lane == 0 && !(i & 1)) PROF(53 + (i >> 1));
                }
                bulk_commit();
                if (lane == 0) PROF(8);
                bulk_wait_read<0>();
                if (lane == 0) PROF(9);
            }
        }
        if (pw < 2) {
            mbar_wait(bars + B_EPO, 0);
            mbar_wait(bars + B_XF, 0);
            const int novf = min(lds32(bars + MI_NOVF), (uint32_t)OVCAP);
#pragma unroll 1
            for (int o = OB * pw; o < novf; o += 2 * OB) {
                const int n = min(novf - o, OB);
                uint32_t w = lds32(bars + MI_OVF + (o + min(lane, n - 1)) * 4);
                int rk = 0;
#pragma unroll 1
                for (int j = 0; j < n; ++j) { const uint32_t y = __shfl_sync(0xffffffffu, w, j); rk += y < w || (y == w && j < lane); }
                if (lane < n) sts32(bars + MI_OVF + (o + rk) * 4, w);
                __syncwarp();
                w = lds32(bars + MI_OVF + (o + min(lane, n - 1)) * 4);
                const uint32_t more = __ballot_sync(0xffffffffu, (((__shfl_down_sync(0xffffffffu, w, 1) ^ w) >> 14) == 0) & (lane + 1 < n));
                const uint32_t f = __ldg((const unsigned short*)p.dis + (w >> 14)) * 0x10001u;
                mbar_wait(bars + B_HV, 0);
                uint4 v[OB];
#pragma unroll
                for (int i = 0; i < OB; i += 3) {
                    if (i < n) {
#pragma unroll
                        for (int j = i; j < i + 3; ++j) {
                            const uint32_t s = __shfl_sync(0xffffffffu, w, j) & 0x3fffu;
                            v[j] = make_uint4(0, 0, 0, 0);
                            if (j < n) v[j] = ldg_sc(p.H + lane * N + s);
                        }
#pragma unroll
                        for (int j = i; j < i + 3; ++j) {
                            const uint32_t fj = __shfl_sync(0xffffffffu, f, j);
                            v[j] = make_uint4(hmul2(v[j].x, fj), hmul2(v[j].y, fj), hmul2(v[j].z, fj), hmul2(v[j].w, fj));
                            if (j && (more >> (j - 1) & 1)) v[j] = make_uint4(hadd2(v[j].x, v[j - 1].x), hadd2(v[j].y, v[j - 1].y), hadd2(v[j].z, v[j - 1].z), hadd2(v[j].w, v[j - 1].w));
                        }
                    }
                }
                mbar_wait(bars + B_RV, 0);
                const uint32_t go = __ballot_sync(0xffffffffu, lane < n && !ld_relaxed(p.sync + SY_SLOW + (w >> 14) / NPC)) & ~more;
#pragma unroll
                for (int j = 0; j < OB; ++j)
                    if (go >> j & 1) red_row(p.out + (__shfl_sync(0xffffffffu, w, j) >> 14) * 32 + lane, v[j]);
            }
            if (lane == 0) PROF(pw ? 48 : 44);
        }
    } else {
        const int g = lane >> 2, t = lane & 3;
        const int wi = warp < GW ? warp + LW : warp - GW;
        if (warp < GW) {
            const int wg = warp >> 2, w4 = warp & 3;
            uint32_t h[20];
            sts32(bars + MI_TOUCH, (uint32_t)(uint64_t)p.dis ^ p.Ee);
            if (rowcta) {
#pragma unroll
                for (int j = 0; j < 10; ++j) h[j] = __ldg((const uint32_t*)p.dis + (node0 >> 1) + 4 * j + t);
            }
            bar_sync(0, GT + 128);
            {
                const int cw = (w4 - wg * (MW == 1 ? 1 : MW == 2 ? 2 : 0)) & 3;
                if (cw < MW) {
                    const uint32_t qa = sS + A3 * UNIT + wg * 2048 + (lane & 15) * 128 + (((lane >> 4) ^ (lane & 7)) << 4);
                    const uint32_t ka = sS + (A3 + 1) * UNIT + wg * 4096 + (cw * (32 / MW) + (lane & 7)) * 128 + (((lane >> 3) ^ (lane & 7)) << 4);
                    mbar_wait(bars + B_QK, 0);
                    __syncwarp();
                    if (tid == 0) PROF(33);
                    const uint4 a0 = ldsm4(qa), a1 = ldsm4(qa ^ 32), a2 = ldsm4(qa ^ 64), a3 = ldsm4(qa ^ 96);
                    uint4 bb[4 / MW][2];
#pragma unroll
                    for (int nb = 0; nb < 4 / MW; ++nb) { bb[nb][0] = ldsm4(ka + nb * 1024); bb[nb][1] = ldsm4((ka ^ 64) + nb * 1024); }
#pragma unroll
                    for (int nb = 0; nb < 4 / MW; ++nb) {
                        const uint4 b0 = bb[nb][0], b1 = bb[nb][1];
                        float c[4] = {0.f, 0.f, 0.f, 0.f}, e[4] = {0.f, 0.f, 0.f, 0.f};
                        mma16816(c, a0.x, a0.y, a0.z, a0.w, b0.x, b0.y); mma16816(e, a1.x, a1.y, a1.z, a1.w, b0.z, b0.w);
                        mma16816(c, a2.x, a2.y, a2.z, a2.w, b1.x, b1.y); mma16816(e, a3.x, a3.y, a3.z, a3.w, b1.z, b1.w);
                        const uint32_t rp = sb + SM_X + ((wg * 16 + g) * 32 + (((cw * (4 / MW) + nb + g) & 3) * 8) + 2 * t) * 4;
                        sts64(rp, __float_as_uint(c[0] + e[0]), __float_as_uint(c[1] + e[1]));
                        sts64(rp + 1024, __float_as_uint(c[2] + e[2]), __float_as_uint(c[3] + e[3]));
                    }
                }
                bar_arrive(1, GT + 128);
            }
            if (rowcta) {
                float d[40];
                const uint32_t uw = sS + wg * UNIT, fb = bars + B_F;
                fence_async_smem();
                mbar_wait(bars + B_SENT, 0);
                if (tid == 0) PROF(35);
                gemm_quarter<0>(d, uw + A0 * UNIT, sT, bars + B_K, 0);
                if (tid == 0) PROF(10);
                gemm_quarter<1>(d, uw + A1 * UNIT, sT, bars + B_K, 0, fb);
                gemm_quarter<2>(d, uw + A2 * UNIT, sT, bars + B_K, 0, fb + 8);
                gemm_quarter<3>(d, uw + A4 * UNIT, sT, bars + B_K, 0, fb + 16);
                wg_wait<0>(); warp_arrive(fb + 24);
                if (tid == 0) PROF(11);
#pragma unroll
                for (int j = 9; j >= 0; --j) {
                    const float s0 = blo(h[j]), s1 = bhi(h[j]);
                    h[2 * j + 1] = pack_bf16(d[4 * j + 2] * s0, d[4 * j + 3] * s1);
                    h[2 * j]     = pack_bf16(d[4 * j] * s0, d[4 * j + 1] * s1);
                }
                mbar_wait(fb + 24, 0);
                __syncwarp();
                {
                    const uint32_t sa = sS + A4 * UNIT + warp * 2560 + (lane & 8) * 160 + (lane >> 4) * 128 + (lane & 7) * 16;
#pragma unroll
                    for (int i = 0; i < 5; ++i) stsm4t(sa + i * 256, h[4 * i], h[4 * i + 1], h[4 * i + 2], h[4 * i + 3]);
                }
                warp_arrive(bars + B_HS);
                if (tid == 0) PROF(60);
                uint4 e3 = make_uint4(0, 0, 0, 0);
                if (stage) e3 = ldg_in(p.esrc + (node0 + 16 * wg + 12 + w4) * 4);
                gemm_quarter<0>(d, uw + A0 * UNIT, sT, bars + B_K, 1);
                if (tid == 0) PROF(12);
                gemm_quarter<1>(d, uw + A1 * UNIT, sT, bars + B_K, 1, fb + 32);
                gemm_quarter<2>(d, uw + A2 * UNIT, sT, bars + B_K, 1, fb + 40);
                mbar_wait(bars + B_LF, 0);
                const uint32_t ebad = lds32(bars + MI_EBAD);
                gemm_quarter<3>(d, uw + A0 * UNIT, sT, bars + B_K, 1, fb + 48);
                if (tid == 0) PROF(13);
                wg_wait<0>(); warp_arrive(fb + 56);
                if (tid == 0) PROF(14);
                pack_acc(h, d);
                mbar_wait(fb + 32 + wg * 8, 0);
                __syncwarp();
                store_tile(h, sT, wg, w4, lane);
                warp_arrive(bars + B_Q);
                auto stage3 = [&]() {
                    mbar_wait(fb + 56, 0);
                    if (stage && elect()) {
                        const uint32_t dst = uw + A0 * UNIT + w4 * 2048, bar = bars + B_A + (4 * wg + 3) * 8;
                        mbar_expect(bar, 2048);
                        tma2d(dst, &tmG, 0, e3.x, bar);        tma2d(dst + 512, &tmG, 0, e3.y, bar);
                        tma2d(dst + 1024, &tmG, 0, e3.z, bar); tma2d(dst + 1536, &tmG, 0, e3.w, bar);
                    }
                };
                const uint32_t rows = uw + (w4 & 1) * 4096 + (lane & 4) * 512 + (lane & 8) * 64 + (((lane ^ (lane >> 2 & 4)) & 7) << 4);
#pragma unroll 1
                for (int c2 = 0; c2 < 4; c2 += 2) {
                    const int c = (w4 >> 1) + c2;
                    const int n = 16 * wg + 4 * c + 2 * (w4 & 1);
                    if (stage) mbar_wait(bars + B_A + (4 * wg + c) * 8, 0);
                    if (tid == 0) PROF(c ? 50 : 15);
                    if (tid == 96) PROF(c == 1 ? 51 : 52);
                    if (!ebad) {
                        const uint32_t ra = rows + (A_TILES >> (8 * c) & 255) * UNIT;
                        uint4 r[2][4];
#pragma unroll
                        for (int kb = 0; kb < 4; ++kb) { r[0][kb] = ldsm4(ra + kb * 128); r[1][kb] = ldsm4(ra + 1024 + kb * 128); }
                        warp_arrive(bars + B_FA + c * 8);
                        if (c2 == 0) { stage3(); mbar_wait(bars + B_Q, 0); }
                        __syncwarp();
                        attention_frags(r, sT, n, lane);
                    } else {
                        warp_arrive(bars + B_FA + c * 8);
                        if (c < 2) stage3();
                        mbar_wait(bars + B_Q, 0);
                        attention_generic(p, sT, n, node0 + n, lane); attention_generic(p, sT, n + 1, node0 + n + 1, lane);
                    }
                }
                fence_async_smem();
                warp_arrive(bars + B_Z);
                if (tid == 0) PROF(16);
                mbar_wait(bars + B_K, 0);
                if (tid == 0) PROF(17);
                gemm_quarter<0>(d, uw + A3 * UNIT, sT, bars + B_Z, 0);
                gemm_quarter<1>(d, uw + A1 * UNIT, sT, bars + B_K, 0, fb + 64);
                gemm_quarter<2>(d, uw + A2 * UNIT, sT, bars + B_K, 0, fb + 72);
                {
                    mbar_wait(bars + B_K + 24, 0);
                    __syncwarp();
                    const uint32_t a = desc_lo(sS + A5 * UNIT + wg * 2048), b = desc_lo(sT) + ((3 * KB) >> 4);
                    wg_fence();
                    wgmma80<false>(d, a, b);            wg_commit(); wg_wait<1>(); warp_arrive(fb + 80);
                    wgmma80<false>(d, a + 512, b + 2);  wg_commit(); wg_wait<1>(); warp_arrive(fb + 88);
                    wgmma80<false>(d, a + 1024, b + 4);
                    wgmma80<false>(d, a + 1536, b + 6); wg_commit();
                }
                wg_wait<0>(); warp_arrive(bars + B_VE);
                if (tid == 0) PROF(18);
                pack_acc(h, d);
                mbar_wait(wg == 3 ? bars + B_VE : fb + 64 + wg * 8, 0);
                __syncwarp();
                store_tile(h, sT, wg, w4, lane);
                warp_arrive(bars + B_R);
                if (tid == 0) PROF(19);
            }
        } else {
            const int lw = warp - GW, tl = tid - GT;
            uint32_t dd[5], ss[5];
            const int e0 = cta * p.chunk;
            {
                const int last = max(p.Efast - 2, 0);
                const uint32_t ea = min(e0 + 2 * tl, last), eb = min(e0 + 2 * tl + 2 * LT, last), ec = min(e0 + tl + 4 * LT, last + 1);
                const int2 d0 = __ldg((const int2*)(p.dst + ea)), d1 = __ldg((const int2*)(p.dst + eb));
                dd[4] = __ldg(p.dst + ec);
                const int2 s0 = __ldg((const int2*)(p.src + ea)), s1 = __ldg((const int2*)(p.src + eb));
                ss[4] = __ldg(p.src + ec);
                dd[0] = d0.x; dd[1] = d0.y; dd[2] = d1.x; dd[3] = d1.y; ss[0] = s0.x; ss[1] = s0.y; ss[2] = s1.x; ss[3] = s1.y;
            }
            const uint32_t epoch = ld_relaxed(p.sync + (cta & 15) * 32);
            int4 ed = make_int4(0, 0, 0, 0), es = make_int4(0, 0, 0, 0);
            if (stage) {
                ed = __ldg((const int4*)p.edst4 + (uint32_t)(node0 + min(tl, NPC - 1)));
                es = __ldg((const int4*)p.esrc + (uint32_t)(node0 + 64 + (tl >> 4)));
            }
            {
                const uint32_t lo = (tl & 3) * 0x40004000u, hi = (NPC * 2 + (cta & 7)) * 0x010101u;
#pragma unroll
                for (int r = 0; r < 2; ++r) {
                    sts128(sb + X_OUT + (tl + r * LT) * 16, make_uint4(lo, lo, (lo & 0xffffu) | hi << 16, hi));
                    sts128(sb + X_IMG + (tl + r * LT) * 16, make_uint4(0, 0, 0, 0));
                }
            }
            if (tl < 32) sts128(bars + MI_PCNT + tl * 16, make_uint4(0, 0, 0, 0));
            if (tl == 32) { sts32(bars + MI_SLOW, p.chunk == 0); sts32(bars + MI_EBAD, !p.edst4); sts32(bars + MI_NOVF, 0); sts32(bars + MI_FLAGS, 0); }
            bar_sync(2, LT);
            if (tl == 0) PROF(34);
            const int zero = lds32(bars + MI_PCNT + 127 * 4);
            const int ne = min(p.chunk, p.Efast - e0) + zero;
            uint32_t q[5], nx = 0, ox = 0;
            {
                uint32_t c[5];
#pragma unroll
                for (int k = 0; k < 5; ++k) {
                    dd[k] = (k < 4 ? 2 * tl + (k >> 1) * 2 * LT : tl + 4 * LT) < ne ? dd[k] : (RCTA + (lane & 1)) * NPC;
                    c[k] = dd[k] / NPC;
                    q[k] = atoms_add(bars + MI_PCNT + c[k] * 4, c[k] < RCTA);
                }
                if (tl == 0) PROF(36);
#pragma unroll
                for (int k = 0; k < 5; ++k) {
                    const uint32_t w = (((dd[k] - c[k] * NPC) * 8 + (ss[k] & 7u)) << 14) + ss[k] + 8;
                    uint32_t sl = (q[k] >> 2) + ((c[k] >> 3) & 3u);
                    sl = min(sl, sl - 5);
                    const uint32_t ca = sb + X_OUT + c[k] * 64 + ((q[k] + (c[k] >> 1)) & 3u) * 16 + sl;
                    if (q[k] < CELLN) { sts16(ca + sl, w); asm volatile("st.shared.u8 [%0 + 10], %1;" :: "r"(ca), "r"(w >> 16) : "memory"); }
                    nx += q[k] >= CELLN;
                }
                if (nx) ox = atoms_add(bars + MI_NOVF, nx);
                const int nz = node0 + tl + zero;
                if (stage && tl < NPC && ((ed.x != nz) | (ed.y != nz) | (ed.z != nz) | (ed.w != nz))) sts32(bars + MI_FLAGS, W_EBAD);
            }
            if (tl == 0) PROF(37);
            bar_sync(4, LT + 128);
            if (tl == 0) PROF(24);
            const uint32_t tag = ((epoch + zero) % 31u + 1u) << 27;
            {
                const uint32_t fl = lds32(bars + MI_FLAGS) | tag | (lds32(bars + MI_NOVF) > OVCAP / 2 ? W_OVF : 0u);
                uint4* const gp = p.cells + ((tl >> 2) * NCTA + cta) * 4 + (tl & 3);
#pragma unroll
                for (int r = 0; r < 2; ++r) {
                    uint4 w = lds128(sb + X_OUT + (tl + r * LT) * 16);
                    w.w |= fl;
                    if (r == 0 || tl + LT < RCTA * 4) gp[r * (LT / 4) * NCTA * 4] = w;
                }
            }
            warp_arrive(bars + B_SENT);
            if (tl == 0) { sts32(bars + MI_EPOCH, epoch); mbar_arrive(bars + B_EPO); }
            if (tl == 0) PROF(25);
#pragma unroll
            for (int k = 0; k < 5; ++k) {
                if (q[k] >= CELLN) sts32(bars + MI_OVF + min(ox, (uint32_t)OVCAP - 1) * 4, dd[k] << 14 | ss[k]);
                ox += q[k] >= CELLN;
            }
            uint4 r[4][2];
            auto load_rows = [&]() {
                if (stage) {
                    const char* xl = p.x + (lane & 15) * 16;
                    const char* r0 = row_ptr(xl, es.x); const char* r1 = row_ptr(xl, es.y); const char* r2 = row_ptr(xl, es.z); const char* r3 = row_ptr(xl, es.w);
                    r[0][0] = ldg_in(r0); r[0][1] = ldg_in(r0 + 256); r[1][0] = ldg_in(r1); r[1][1] = ldg_in(r1 + 256);
                    r[2][0] = ldg_in(r2); r[2][1] = ldg_in(r2 + 256); r[3][0] = ldg_in(r3); r[3][1] = ldg_in(r3 + 256);
                }
            };
            auto attend = [&]() {
                mbar_wait(bars + B_Q, 0);
                __syncwarp();
                if (!lds32(bars + MI_EBAD)) attention_chunks(r, sT, 64 + 2 * lw, lane);
                else { attention_generic(p, sT, 64 + 2 * lw, node0 + 64 + 2 * lw, lane); attention_generic(p, sT, 65 + 2 * lw, node0 + 65 + 2 * lw, lane); }
                fence_async_smem();
                warp_arrive(bars + B_Z);
                if (tl == 0) PROF(32);
            };
            if (rowcta) {
                mbar_wait(bars + B_SENT, 0);
                if (tl == LT - 1) sts32(sb + X_TAB + NPC * 64, 64);
                if (tl < 128) sts128(sb + X_ZERO + tl * 16, make_uint4(0, 0, 0, 0));
                uint4 c0, c1;
                const uint4* cp = p.cells + cta * (NCTA * 4) + tl;
                mbar_wait(bars + B_CGO, 0);
#pragma unroll 1
                for (int it = 0;; ++it) {
                    c0 = ld_relaxed4(cp); c1 = ld_relaxed4(cp + LT);
                    if (!__any_sync(0xffffffffu, ((c0.w ^ tag) | (c1.w ^ tag)) >> 27) || it >= SPIN_LIMIT) break;
                }
                if (tl == 0) PROF(26);
                if ((c0.w | c1.w) & W_OVF)  sts32(bars + MI_SLOW, 1);
                if ((c0.w | c1.w) & W_EBAD) sts32(bars + MI_EBAD, 1);
                uint32_t w[10] = {__byte_perm(c0.x, c0.z, 0x6610), __byte_perm(c0.x, c0.z, 0x7732), __byte_perm(c0.y, c0.w, 0x4410), __byte_perm(c0.y, c0.w, 0x5532), __byte_perm(c0.z, c0.w, 0x6610),
                                  __byte_perm(c1.x, c1.z, 0x6610), __byte_perm(c1.x, c1.z, 0x7732), __byte_perm(c1.y, c1.w, 0x4410), __byte_perm(c1.y, c1.w, 0x5532), __byte_perm(c1.z, c1.w, 0x6610)};
                {
                    uint32_t c[10];
#pragma unroll
                    for (int m = 0; m < 10; ++m) {
                        const uint32_t a = (w[m] >> 12) & 0xffcu;
                        c[m] = atoms_add(sb + X_CNT + a, a < NPC * 32);
                        w[m] = (w[m] & 0x3fffu) + (a << 15);
                    }
#pragma unroll
                    for (int m = 0; m < 10; ++m) w[m] += (c[m] > 7 ? 0x20000u : c[m]) << 14;
                }
                bar_sync(2, LT);
                if (tl == 0) { mbar_arrive(bars + B_LF); PROF(27); }
                if (lw < 3) {
                    const int d0 = min(tl, NPC - 8 + (tl & 7));
                    const int dl = d0 ^ ((d0 >> 3) & 1);
                    const uint4 n0 = lds128(sb + X_CNT + dl * 32), n1 = lds128(sb + X_CNT + dl * 32 + 16);
                    uint32_t pk = min(n0.x, 8u) + (min(n0.y, 8u) << 4) + (min(n0.z, 8u) << 8) + (min(n0.w, 8u) << 12) +
                                  (min(n1.x, 8u) << 16) + (min(n1.y, 8u) << 20) + (min(n1.z, 8u) << 24) + (min(n1.w, 8u) << 28);
                    pk = __funnelshift_r(pk, pk, 4 * lane);
                    uint32_t du = 0xf0000000u, ru = 0, b[8] = {0, 0, 0, 0, 0, 0, 0, 0};
                    auto code2 = [&](uint32_t b0, uint32_t b1) {
                        return __byte_perm(__float_as_uint(__uint_as_float(b0) * 8388608.f), __float_as_uint(__uint_as_float(b1) * 8388608.f), 0x7632);
                    };
                    uint32_t ta = (lane + 7) * 8;
                    auto pass_on = [&]() {
                        ru = __shfl_sync(0xffffffffu, ru, lane + 1, 8);
                        const uint32_t t0 = (code2(b[0], b[2]) >> 7) + code2(b[1], b[3]) * 2, t1 = (code2(b[4], b[6]) >> 7) + code2(b[5], b[7]) * 2;
                        asm volatile("st.shared.v2.u32 [%0], {%1, %2};" :: "r"(sb + X_TAB + ((dl * 64) | (ta & 56))), "r"(t0), "r"(t1) : "memory");
                        ta += 8;
                    };
                    auto take = [&](uint32_t& m, uint32_t& bit, uint32_t n, int c) {
                        asm("{\n.reg .pred p;\n.reg .b32 u;\nsetp.gt.u32 p, %2, %3;\nadd.u32 u, %0, -1;\nlop3.b32 %1, %0, u, 0, 0x30;\n@p and.b32 %0, %0, u;\n}"
                            : "+r"(m), "=r"(bit) : "r"(n), "r"(c));
                    };
#pragma unroll 1
                    for (int k = 0; k < 8; ++k) {
                        const uint32_t n = pk & 15u;
                        const bool big = __any_sync(0xffffffffu, n > 6);
                        pk >>= 4;
                        pass_on();
                        const uint32_t fr = ~(du | ru);
                        uint32_t m = fr;
#pragma unroll
                        for (int c = 0; c < 6; ++c) take(m, b[c], n, c);
                        if (big) { take(m, b[6], n, 6); take(m, b[7], n, 7); }
                        du |= m ^ fr;
                        ru |= m ^ fr;
                    }
                    pass_on();
                    sts32(sb + X_RU + d0 * 4, ru);
                }
                if (tl == 0) PROF(49);
                mbar_wait(bars + B_MI, 0); mbar_wait(bars + B_K + 8, 1);
                load_rows();
                bar_sync(2, LT);
                if (tl == 0) PROF(28);
                const int v = LT - 1 - tl;
                if (lw >= 6 && v < 40) {
                    const uint4 b = lds128(sb + X_RU + (v >> 2) * 32), e = lds128(sb + X_RU + (v >> 2) * 32 + 16);
                    const uint32_t f2 = b.x & b.y & b.z & b.w;
                    const uint32_t s0 = (f2 & e.x) | (~f2 & b.x), s1 = (f2 & e.y) | (~f2 & b.y), s2 = (f2 & e.z) | (~f2 & b.z);
                    const uint32_t f1 = s0 & s1, f0 = (f1 & s2) | (~f1 & s0);
                    uint32_t u[4];
#pragma unroll
                    for (int k = 0; k < 4; ++k) {
                        const int sh = (v & 3) * 8 + 2 * k;
                        u[k] = ((((f0 >> sh) & 3u) * 0x8001u) & 0x10001u) + ((((f1 >> sh) & 3u) * 0x10002u) & 0x20002u) + ((((f2 >> sh) & 3u) * 0x20004u) & 0x40004u);
                    }
                    sts128(sb + X_DEF + v * 16, make_uint4(u[0], u[1], u[2], u[3]));
                }
                {
                    uint32_t rd[10];
#pragma unroll
                    for (int m = 0; m < 10; ++m) asm volatile("ld.shared.u8 %0, [%1];" : "=r"(rd[m]) : "r"(sb + X_TAB + min(w[m] >> 14, NPC * 64u)) : "memory");
#pragma unroll
                    for (int m = 0; m < 10; ++m) {
                        rd[m] -= 1;
                        if (rd[m] < 48) sts16(sb + X_IMG + ((w[m] >> 14) & ~63u) + min(rd[m], 31u) * 2, w[m] & 0x3fffu);
                        w[m] |= rd[m] & 0x80000000u;
                    }
                    if (__any_sync(0xffffffffu, (int)(w[0] | w[1] | w[2] | w[3] | w[4] | w[5] | w[6] | w[7] | w[8] | w[9]) < 0)) {
                        uint32_t n = 0;
#pragma unroll
                        for (int m = 0; m < 10; ++m) n += w[m] >> 31;
                        uint32_t o = atoms_add(bars + MI_NOVF, n);
#pragma unroll
                        for (int m = 0; m < 10; ++m) {
                            if ((int)w[m] < 0) sts32(bars + MI_OVF + min(o, (uint32_t)OVCAP - 1) * 4, ((w[m] >> 6) & 0x1fc000u) + (w[m] & 0x3fffu) + (node0 * 16384 - 8));
                            o += w[m] >> 31;
                        }
                    }
                }
                bar_sync(2, LT);
                if (tl == 0) PROF(29);
#pragma unroll 1
                for (int set = lw; set < 10; set += lw >= 3 && lw < 5 ? 5 : 10) publish(set);
            }
            warp_arrive(bars + B_XF);
            if (tl == 0) PROF(30);
            if (rowcta) attend();
        }
        Unit x0, x1;
        const uint4* ip = p.idx + quarter * (UPQ * 64) + lane;
        auto fetch = [&](Unit& x, int j) { x.a = ld_relaxed4(ip + j * 64); x.b = ld_relaxed4(ip + j * 64 + 32); };
        mbar_wait(bars + B_GO, 0);
        fetch(x0, wi);
        const uint32_t stg = sb + SM_X + (lane & 15) * 16;
        const uint32_t lt = list_tag(lds32(bars + MI_EPOCH)), base = sS - (lt & 0xffffu) * 16;
        const int nu = UPQ + (quarter == 3);
        int u = wi;
        auto unit = [&](Unit& c, Unit& n) {
#pragma unroll 1
            for (int it = 0;; ++it) {
                if (!__any_sync(0xffffffffu, unit_stale(c, lt) > (it < SPIN_LIMIT ? 0u : 0xffffu))) break;
                fetch(c, u);
            }
            if (u >= 4 * AW) { mbar_wait(bars + B_TF, 0); __syncwarp(); }
            if (u + AW < nu) fetch(n, u + AW);
            agg_unit(c, base, stg + u * 256, lt);
            warp_arrive(bars + B_RND + min((u * 171) >> 11, 12) * 8);
            u += AW;
        };
        mbar_wait(bars + B_S, 0);
        if (rowcta) mbar_wait(bars + B_VE, 0);
        __syncwarp();
        if (tid == 0) PROF(20);
        if (tid == GT) PROF(4);
#pragma unroll 1
        for (;;) {
            unit(x0, x1);
            if (u >= nu) break;
            unit(x1, x0);
            if (u >= nu) break;
        }
        if (tid == 0) PROF(21);
        if (rowcta && slow_cta()) { mbar_wait(bars + B_RV, 0); local_generic(p, node0, wi, lane); }
    }
    PROF_FLUSH();
}

typedef CUresult (*EncodeFn)(CUtensorMap*, CUtensorMapDataType, cuuint32_t, void*, const cuuint64_t*, const cuuint64_t*,
                             const cuuint32_t*, const cuuint32_t*, CUtensorMapInterleave, CUtensorMapSwizzle,
                             CUtensorMapL2promotion, CUtensorMapFloatOOBfill);

static void make_map(EncodeFn enc, CUtensorMap* m, const void* ptr, int rows, int box_cols, int box_rows) {
    cuuint64_t dims[2] = {(cuuint64_t)D, (cuuint64_t)rows};
    cuuint64_t strides[1] = {(cuuint64_t)D * 2};
    cuuint32_t box[2] = {(cuuint32_t)box_cols, (cuuint32_t)box_rows};
    cuuint32_t es[2] = {1u, 1u};
    enc(m, CU_TENSOR_MAP_DATA_TYPE_BFLOAT16, 2, const_cast<void*>(ptr), dims, strides, box, es, CU_TENSOR_MAP_INTERLEAVE_NONE,
        box_cols == 64 ? CU_TENSOR_MAP_SWIZZLE_128B : CU_TENSOR_MAP_SWIZZLE_NONE,
        box_cols == 64 ? CU_TENSOR_MAP_L2_PROMOTION_L2_128B : CU_TENSOR_MAP_L2_PROMOTION_NONE, CU_TENSOR_MAP_FLOAT_OOB_FILL_NONE);
}
static void make_map3(EncodeFn enc, CUtensorMap* m, const void* ptr, int rows, int box_rows) {
    cuuint64_t dims[3] = {64, (cuuint64_t)rows, 4};
    cuuint64_t strides[2] = {(cuuint64_t)D * 2, 128};
    cuuint32_t box[3] = {64u, (cuuint32_t)box_rows, 4u};
    cuuint32_t es[3] = {1u, 1u, 1u};
    enc(m, CU_TENSOR_MAP_DATA_TYPE_BFLOAT16, 3, const_cast<void*>(ptr), dims, strides, box, es, CU_TENSOR_MAP_INTERLEAVE_NONE,
        CU_TENSOR_MAP_SWIZZLE_128B, CU_TENSOR_MAP_L2_PROMOTION_L2_256B, CU_TENSOR_MAP_FLOAT_OOB_FILL_NONE);
}

}

extern "C" void kernel_launch(void* const* d_in, const int* in_sizes, int n_in, void* d_out, int out_size) {
    using namespace gk;
    (void)n_in; (void)out_size;
    static EncodeFn enc = nullptr;
    static void *m_ptr, *cells_ptr, *sync_ptr, *h_ptr, *idx_ptr;
    if (!enc) {
        void* fn = nullptr;
        cudaDriverEntryPointQueryResult qr;
        cudaGetDriverEntryPoint("cuTensorMapEncodeTiled", &fn, cudaEnableDefault, &qr);
        enc = (EncodeFn)fn;
        cudaGetSymbolAddress(&m_ptr, g_M);
        cudaGetSymbolAddress(&cells_ptr, g_cells);
        cudaGetSymbolAddress(&sync_ptr, g_sync);
        cudaGetSymbolAddress(&h_ptr, g_H);
        cudaGetSymbolAddress(&idx_ptr, g_idx);
        cudaFuncSetAttribute(fused_kernel, cudaFuncAttributeMaxDynamicSharedMemorySize, SM_ALLOC);
    }
    if (in_sizes[5] != N || in_sizes[0] != N * D) return;
    Params p;
    p.src  = (const int*)d_in[1];
    p.dst  = (const int*)d_in[2];
    p.esrc = (const int*)d_in[3];
    p.edst = (const int*)d_in[4];
    p.sync = (uint32_t*)sync_ptr;
    p.x    = (const char*)d_in[0];
    p.dis  = (const __nv_bfloat16*)d_in[5];
    p.wv   = (const char*)d_in[9];
    p.cells = (uint4*)cells_ptr;
    p.H    = (uint4*)h_ptr;
    p.idx  = (uint4*)idx_ptr;
    p.M    = (uint2*)m_ptr;
    p.out  = (uint4*)d_out;
    p.E  = in_sizes[1];
    p.Ee = in_sizes[3];
    const int chunk = (((p.E + NCTA - 1) / NCTA) + 1) & ~1;
    const bool force_slow = chunk > 5 * LT || (p.E & 1) || p.E < 2;
    p.chunk = force_slow ? 0 : chunk;
    p.edst4 = p.Ee == 4 * N ? p.edst : nullptr;
    if (p.E < 2) p.src = p.dst = (const int*)d_in[0];
    p.Efast = force_slow ? 0 : p.E;

    CUtensorMap tmX, tmWl, tmM, tmWv, tmR, tmO, tmG, tmQ, tmK, tmV3;
    make_map(enc, &tmX, d_in[0], N, 64, NPC);
    make_map3(enc, &tmWl, d_in[6], D, 64);
    make_map3(enc, &tmM, m_ptr, D, 64);
    make_map3(enc, &tmWv, d_in[9], D, 64);
    make_map(enc, &tmR, d_out, N, 64, 16);
    make_map(enc, &tmO, d_out, N, 8, 192);
    make_map(enc, &tmG, d_in[0], N, 256, 1);
    make_map3(enc, &tmQ, d_in[7], D, 16);
    make_map3(enc, &tmK, d_in[8], D, 32);
    make_map3(enc, &tmV3, d_in[9], D, 16);
    fused_kernel<<<NCTA, NTHR, SM_ALLOC, cudaStreamPerThread>>>(p, tmX, tmWl, tmM, tmWv, tmR, tmO, tmG, tmQ, tmK, tmV3);
}
```

```cpp
#include <cuda_runtime.h>
#include <cuda_bf16.h>
#include <cuda.h>
#include <stdint.h>

#define PROFILE 0

namespace gk {

constexpr int N      = 10000;
constexpr int D      = 256;
constexpr int NPC    = 80;
constexpr int NCTA   = 128;
constexpr int RCTA   = N / NPC;
constexpr int NSET   = N / 8;
constexpr int GW     = 16;
constexpr int LW     = 8;
constexpr int AW     = GW + LW;
constexpr int GT     = GW * 32, LT = LW * 32;
constexpr int NTHR   = (AW + 4) * 32;
constexpr int UPQ    = 156;
constexpr int OVCAP  = 128;
#define SPINB 18
constexpr int SPIN_LIMIT = 1 << SPINB;

constexpr int KB      = NPC * 128;
constexpr int UNIT    = 8192;
constexpr int SM_S    = 0;
constexpr int SM_X    = 20 * UNIT;
constexpr int SM_T    = 23 * UNIT;
constexpr int SM_MISC = SM_T + 4 * KB;
constexpr int SM_END  = SM_MISC + 2464;
constexpr int SLICE_END = 128 + N * 16;
constexpr int X_OUT  = SM_X + UNIT;
constexpr int X_TAB  = X_OUT;
constexpr int X_RU   = X_TAB + NPC * 64 + 16;
constexpr int X_DEF  = X_RU + NPC * 4;
constexpr int X_ZERO = X_OUT + UNIT - 2048;
constexpr int X_IMG  = X_OUT + UNIT;
constexpr int X_CNT  = X_IMG + NPC * 64;
static_assert(X_DEF + 640 <= X_ZERO && X_CNT + NPC * 32 + 128 <= SM_T, "list scratch");
constexpr int B_K = 0, B_QK = 32, B_EPO = 40,
              B_A = 48,
              B_F = 176, B_HS = 272, B_Q = 280, B_R = 288,
              B_GO = 296, B_LF = 304, B_TF = 312,   B_CGO = 328, B_MI = 336, B_HR = 344,
              B_Z = 352,
              B_FA = 360, B_XF = 392, B_SENT = 400, B_S = 408, B_VE = 416,
              B_RND = 424;
constexpr int B_HV = 528, B_RV = 536;
constexpr int MI_EPOCH = 544, MI_EBAD = 548, MI_SLOW = 552, MI_NOVF = 556, MI_FLAGS = 560, MI_TOUCH = 564;
constexpr int MI_OVF  = 1280;
constexpr int MI_ES   = 768;
constexpr int MI_PCNT = 1792;
constexpr int MI_DIS  = 2304;
constexpr int A0 = 0, A1 = 4, A2 = 8, A3 = 12, A4 = 16, A5 = 19;
constexpr uint32_t A_TILES = A3 | A1 << 8 | A2 << 16 | A0 << 24;
#define ER 2
#define XORD 0x04156273
#define MW 2
#define OB 6
#define HPER 160

constexpr uint32_t W_OVF = 1u << 24, W_EBAD = 1u << 25;
constexpr int CELLN = 20;

__device__ uint4         g_cells[RCTA * NCTA * 4];
__device__ uint4         g_H[32 * N];
__device__ uint4         g_idx[NSET * 32];
__device__ __nv_bfloat16 g_M[D * D];
__device__ uint32_t      g_sync[24 * 32];
constexpr int SY_M = 16 * 32, SY_H = 17 * 32, SY_L = 18 * 32, SY_R = 19 * 32, SY_SLOW = 20 * 32;
#define PROF(i) do {} while (0)
#define PROF_FLUSH() do {} while (0)
constexpr int SM_ALLOC = SM_END;
#define JITTER() do {} while (0)
static_assert(SM_ALLOC <= 232448, "shared memory");

struct Params {
    const int* src; const int* dst;
    uint32_t* sync;
    const int* esrc; const int* edst4;
    int Efast, chunk;
    const __nv_bfloat16* dis;
    const char* x; const char* wv;
    uint4* cells; uint2* M;
    uint4* idx; uint4* H; uint4* out;
    const int* edst;
    int E, Ee;
};

__device__ __forceinline__ uint32_t s32(const void* p) { return (uint32_t)__cvta_generic_to_shared(p); }
__device__ __forceinline__ void mbar_init(uint32_t a, uint32_t cnt) { asm volatile("mbarrier.init.shared.b64 [%0], %1;" :: "r"(a), "r"(cnt) : "memory"); }
__device__ __forceinline__ void mbar_arrive(uint32_t a) { asm volatile("mbarrier.arrive.shared.b64 _, [%0];" :: "r"(a) : "memory"); }
__device__ __forceinline__ void mbar_expect(uint32_t a, uint32_t bytes) { asm volatile("mbarrier.arrive.expect_tx.shared.b64 _, [%0], %1;" :: "r"(a), "r"(bytes) : "memory"); }
__device__ __forceinline__ void mbar_wait(uint32_t a, uint32_t parity) {
    JITTER();
    uint32_t ok = 0;
#pragma unroll 1
    for (int it = 0; it < SPIN_LIMIT && !ok; ++it)
        asm volatile("{\n.reg .pred p;\nmbarrier.try_wait.parity.shared.b64 p, [%1], %2;\nselp.u32 %0, 1, 0, p;\n}"
                     : "=r"(ok) : "r"(a), "r"(parity) : "memory");
}
__device__ __forceinline__ bool elect() { JITTER(); uint32_t r; asm volatile("{\n.reg .pred p;\nelect.sync _|p, 0xffffffff;\nselp.u32 %0, 1, 0, p;\n}" : "=r"(r) :: "memory"); return r; }
__device__ __forceinline__ void warp_arrive(uint32_t a) {
    JITTER();
    asm volatile("{\n.reg .pred p;\nelect.sync _|p, 0xffffffff;\n@p mbarrier.arrive.shared.b64 _, [%0];\n}" :: "r"(a) : "memory");
}
__device__ __forceinline__ void bar_sync(int id, int n)   { JITTER(); __syncwarp(); asm volatile("bar.sync %0, %1;"   :: "r"(id), "r"(n) : "memory"); }
__device__ __forceinline__ void bar_arrive(int id, int n) { JITTER(); __syncwarp(); asm volatile("bar.arrive %0, %1;" :: "r"(id), "r"(n) : "memory"); }
__device__ __forceinline__ void fence_async_smem() { asm volatile("fence.proxy.async.shared::cta;" ::: "memory"); }
__device__ __forceinline__ void fence_async_gmem() { asm volatile("fence.proxy.async.global;" ::: "memory"); }
__device__ __forceinline__ void tma2d(uint32_t dst, const CUtensorMap* tm, int c0, int c1, uint32_t bar) {
    asm volatile("cp.async.bulk.tensor.2d.shared::cluster.global.mbarrier::complete_tx::bytes [%0], [%1, {%3, %4}], [%2];"
                 :: "r"(dst), "l"(tm), "r"(bar), "r"(c0), "r"(c1) : "memory");
}
__device__ __forceinline__ void tma3d(uint32_t dst, const CUtensorMap* tm, int row, uint32_t bar) {
    asm volatile("cp.async.bulk.tensor.3d.shared::cluster.global.mbarrier::complete_tx::bytes [%0], [%1, {%4, %3, %4}], [%2];"
                 :: "r"(dst), "l"(tm), "r"(bar), "r"(row), "r"(0) : "memory");
}
__device__ __forceinline__ void tma2d_store(const CUtensorMap* tm, uint32_t src, int c0, int c1) {
    asm volatile("cp.async.bulk.tensor.2d.global.shared::cta.bulk_group [%0, {%2, %3}], [%1];"
                 :: "l"(tm), "r"(src), "r"(c0), "r"(c1) : "memory");
}
__device__ __forceinline__ void tma2d_add(const CUtensorMap* tm, uint32_t src, int c0, int c1) {
    asm volatile("cp.reduce.async.bulk.tensor.2d.global.shared::cta.add.bulk_group [%0, {%2, %3}], [%1];"
                 :: "l"(tm), "r"(src), "r"(c0), "r"(c1) : "memory");
}
__device__ __forceinline__ void bulk_load(uint32_t dst, const void* src, uint32_t bytes, uint32_t bar) {
    asm volatile("cp.async.bulk.shared::cluster.global.mbarrier::complete_tx::bytes [%0], [%1], %2, [%3];"
                 :: "r"(dst), "l"(src), "r"(bytes), "r"(bar) : "memory");
}
__device__ __forceinline__ void bulk_store(void* dst, uint32_t src, uint32_t bytes) {
    asm volatile("cp.async.bulk.global.shared::cta.bulk_group [%0], [%1], %2;" :: "l"(dst), "r"(src), "r"(bytes) : "memory");
}
__device__ __forceinline__ uint32_t clk() { uint32_t c; asm volatile("mov.u32 %0, %%clock;" : "=r"(c) :: "memory"); return c; }
__device__ __forceinline__ void wait_clk(uint32_t t) { while ((int)(clk() - t) < 0) {} }
__device__ __forceinline__ void bulk_commit() { asm volatile("cp.async.bulk.commit_group;" ::: "memory"); }
template <int K> __device__ __forceinline__ void bulk_wait_read() { asm volatile("cp.async.bulk.wait_group.read %0;" :: "n"(K) : "memory"); }
__device__ __forceinline__ void prefetch_map(const CUtensorMap* tm) { asm volatile("prefetch.tensormap [%0];" :: "l"(tm) : "memory"); }
__device__ __forceinline__ uint4 lds128(uint32_t a) { uint4 v; asm volatile("ld.shared.v4.u32 {%0,%1,%2,%3}, [%4];" : "=r"(v.x), "=r"(v.y), "=r"(v.z), "=r"(v.w) : "r"(a) : "memory"); return v; }
__device__ __forceinline__ void sts128(uint32_t a, uint4 v) { asm volatile("st.shared.v4.u32 [%0], {%1,%2,%3,%4};" :: "r"(a), "r"(v.x), "r"(v.y), "r"(v.z), "r"(v.w) : "memory"); }
__device__ __forceinline__ float4 lds128f(uint32_t a) { const uint4 v = lds128(a); return make_float4(__uint_as_float(v.x), __uint_as_float(v.y), __uint_as_float(v.z), __uint_as_float(v.w)); }
__device__ __forceinline__ void sts64(uint32_t a, uint32_t x, uint32_t y) { asm volatile("st.shared.v2.u32 [%0], {%1, %2};" :: "r"(a), "r"(x), "r"(y) : "memory"); }
__device__ __forceinline__ uint32_t lds32(uint32_t a) { uint32_t v; asm volatile("ld.shared.u32 %0, [%1];" : "=r"(v) : "r"(a) : "memory"); return v; }
__device__ __forceinline__ void sts32(uint32_t a, uint32_t v) { asm volatile("st.shared.u32 [%0], %1;" :: "r"(a), "r"(v) : "memory"); }
__device__ __forceinline__ void sts16(uint32_t a, uint32_t v) { asm volatile("st.shared.u16 [%0], %1;" :: "r"(a), "h"((unsigned short)v) : "memory"); }
__device__ __forceinline__ uint32_t atoms_add(uint32_t a, uint32_t x) { uint32_t v; asm volatile("atom.shared.add.u32 %0, [%1], %2;" : "=r"(v) : "r"(a), "r"(x) : "memory"); return v; }
__device__ __forceinline__ uint32_t ld_relaxed(const uint32_t* p) { uint32_t v; asm volatile("ld.relaxed.gpu.global.u32 %0, [%1];" : "=r"(v) : "l"(p) : "memory"); return v; }
__device__ __forceinline__ uint4 ld_relaxed4(const uint4* p) { uint4 v; asm volatile("ld.relaxed.gpu.global.L1::no_allocate.v4.u32 {%0,%1,%2,%3}, [%4];" : "=r"(v.x), "=r"(v.y), "=r"(v.z), "=r"(v.w) : "l"(p) : "memory"); return v; }
__device__ __forceinline__ uint32_t ld_acquire(const uint32_t* p) { uint32_t v; asm volatile("ld.acquire.gpu.global.u32 %0, [%1];" : "=r"(v) : "l"(p) : "memory"); return v; }
__device__ __forceinline__ void st_relaxed(uint32_t* p, uint32_t v) { asm volatile("st.relaxed.gpu.global.u32 [%0], %1;" :: "l"(p), "r"(v) : "memory"); }
__device__ __forceinline__ void red_relaxed(uint32_t* p) { asm volatile("red.relaxed.gpu.global.add.u32 [%0], 1;" :: "l"(p) : "memory"); }
__device__ __forceinline__ uint32_t list_tag(uint32_t epoch) { return (epoch % 3u + 1u) * 0x40004000u; }
__device__ __forceinline__ void red_release(uint32_t* p) { asm volatile("red.release.gpu.global.add.u32 [%0], 1;" :: "l"(p) : "memory"); }
__device__ __forceinline__ void wait_count(const uint32_t* p, uint32_t target) {
#pragma unroll 1
    for (int it = 0; it < SPIN_LIMIT; ++it)
        if ((int)(ld_acquire(p) - target) >= 0) break;
}
__device__ __forceinline__ uint4 ldg_in(const void* p) { uint4 v; asm volatile("ld.global.nc.L1::no_allocate.v4.u32 {%0,%1,%2,%3}, [%4];" : "=r"(v.x), "=r"(v.y), "=r"(v.z), "=r"(v.w) : "l"(p)); return v; }
__device__ __forceinline__ uint4 ldg_sc(const void* p) { uint4 v; asm volatile("ld.global.L1::no_allocate.v4.u32 {%0,%1,%2,%3}, [%4];" : "=r"(v.x), "=r"(v.y), "=r"(v.z), "=r"(v.w) : "l"(p) : "memory"); return v; }
__device__ __forceinline__ void red_row(uint4* p, uint4 v) { asm volatile("red.relaxed.gpu.global.add.noftz.v4.bf16x2 [%0], {%1,%2,%3,%4};" :: "l"(p), "r"(v.x), "r"(v.y), "r"(v.z), "r"(v.w) : "memory"); }
__device__ __forceinline__ uint32_t pack_bf16(float lo, float hi) { uint32_t r; asm("cvt.rn.bf16x2.f32 %0, %1, %2;" : "=r"(r) : "f"(hi), "f"(lo)); return r; }
__device__ __forceinline__ float blo(uint32_t v) { return __uint_as_float(v << 16); }
__device__ __forceinline__ float bhi(uint32_t v) { return __uint_as_float(v & 0xffff0000u); }
__device__ __forceinline__ const char* row_ptr(const char* base, uint32_t row) {
    uint64_t r; asm("mad.wide.u32 %0, %1, 512, %2;" : "=l"(r) : "r"(row), "l"((uint64_t)base)); return (const char*)r;
}

constexpr uint32_t DESC_HI = 64u | (1u << 30);
__device__ __forceinline__ uint32_t desc_lo(uint32_t addr) { return ((addr & 0x3FFFF) >> 4) | (1u << 16); }
__device__ __forceinline__ void wg_fence()  { asm volatile("wgmma.fence.sync.aligned;" ::: "memory"); }
__device__ __forceinline__ void wg_commit() { asm volatile("wgmma.commit_group.sync.aligned;" ::: "memory"); }
template <int K> __device__ __forceinline__ void wg_wait() { asm volatile("wgmma.wait_group.sync.aligned %0;" :: "n"(K) : "memory"); }
#define GK_ACC(c) c(d[0]), c(d[1]), c(d[2]), c(d[3]), c(d[4]), c(d[5]), c(d[6]), c(d[7]), c(d[8]), c(d[9]), \
    c(d[10]), c(d[11]), c(d[12]), c(d[13]), c(d[14]), c(d[15]), c(d[16]), c(d[17]), c(d[18]), c(d[19]), \
    c(d[20]), c(d[21]), c(d[22]), c(d[23]), c(d[24]), c(d[25]), c(d[26]), c(d[27]), c(d[28]), c(d[29]), \
    c(d[30]), c(d[31]), c(d[32]), c(d[33]), c(d[34]), c(d[35]), c(d[36]), c(d[37]), c(d[38]), c(d[39])
#define GK_WGMMA(P) "{\n.reg .pred p;\n.reg .b64 da, db;\nsetp.ne.b32 p, " P ", 0;\nmov.b64 da, {%40, %42};\nmov.b64 db, {%41, %42};\n" \
    "wgmma.mma_async.sync.aligned.m64n80k16.f32.bf16.bf16 " \
    "{%0,%1,%2,%3,%4,%5,%6,%7,%8,%9,%10,%11,%12,%13,%14,%15,%16,%17,%18,%19," \
    "%20,%21,%22,%23,%24,%25,%26,%27,%28,%29,%30,%31,%32,%33,%34,%35,%36,%37,%38,%39}, da, db, p, 1, 1, 1, 0;\n}\n"
template <bool FIRST>
__device__ __forceinline__ void wgmma80(float (&d)[40], uint32_t alo, uint32_t blo_) {
    if (FIRST) asm volatile(GK_WGMMA("0") : GK_ACC("=f") : "r"(alo), "r"(blo_), "r"(DESC_HI));
    else       asm volatile(GK_WGMMA("1") : GK_ACC("+f") : "r"(alo), "r"(blo_), "r"(DESC_HI));
}
template <int KQ>
__device__ __forceinline__ void gemm_quarter(float (&d)[40], uint32_t unit, uint32_t tile, uint32_t bar, uint32_t parity, uint32_t rel = 0) {
    mbar_wait(bar + KQ * 8, parity);
    __syncwarp();
    const uint32_t a = desc_lo(unit), b = desc_lo(tile) + ((KQ * KB) >> 4);
    wg_fence();
    wgmma80<KQ == 0>(d, a, b);
    if (KQ) { wg_commit(); wg_wait<1>(); warp_arrive(rel); }
    wgmma80<false>(d, a + 128, b + 2);
    wgmma80<false>(d, a + 256, b + 4);
    wgmma80<false>(d, a + 384, b + 6);
    wg_commit();
}
__device__ __forceinline__ void stsm4t(uint32_t a, uint32_t r0, uint32_t r1, uint32_t r2, uint32_t r3) {
    asm volatile("stmatrix.sync.aligned.m8n8.x4.trans.shared.b16 [%0], {%1,%2,%3,%4};" :: "r"(a), "r"(r0), "r"(r1), "r"(r2), "r"(r3) : "memory");
}
__device__ __forceinline__ void stsm4(uint32_t a, uint32_t r0, uint32_t r1, uint32_t r2, uint32_t r3) {
    asm volatile("stmatrix.sync.aligned.m8n8.x4.shared.b16 [%0], {%1,%2,%3,%4};" :: "r"(a), "r"(r0), "r"(r1), "r"(r2), "r"(r3) : "memory");
}
__device__ __forceinline__ uint4 ldsm4(uint32_t a) {
    uint4 v; asm volatile("ldmatrix.sync.aligned.m8n8.x4.shared.b16 {%0,%1,%2,%3}, [%4];" : "=r"(v.x), "=r"(v.y), "=r"(v.z), "=r"(v.w) : "r"(a) : "memory"); return v;
}
__device__ __forceinline__ void mma16816(float (&c)[4], uint32_t a0, uint32_t a1, uint32_t a2, uint32_t a3, uint32_t b0, uint32_t b1) {
    asm volatile("mma.sync.aligned.m16n8k16.row.col.f32.bf16.bf16.f32 {%0,%1,%2,%3}, {%4,%5,%6,%7}, {%8,%9}, {%0,%1,%2,%3};"
        : "+f"(c[0]), "+f"(c[1]), "+f"(c[2]), "+f"(c[3]) : "r"(a0), "r"(a1), "r"(a2), "r"(a3), "r"(b0), "r"(b1));
}
__device__ __forceinline__ void pack_acc(uint32_t (&h)[20], const float (&d)[40]) {
#pragma unroll
    for (int i = 0; i < 20; ++i) h[i] = pack_bf16(d[2 * i], d[2 * i + 1]);
}
__device__ __forceinline__ void store_tile(const uint32_t (&h)[20], uint32_t tile, int mt, int w4, int lane) {
    const int r = lane & 7;
    const uint32_t base = tile + mt * KB + (((lane >> 4) * 8 + r) * 128) + (((2 * w4 + ((lane >> 3) & 1)) ^ r) << 4);
#pragma unroll
    for (int i = 0; i < 5; ++i) stsm4t(base + i * 2048, h[4 * i], h[4 * i + 1], h[4 * i + 2], h[4 * i + 3]);
}
__device__ __forceinline__ void fma8(float (&a)[8], float w, const uint4& v) {
    a[0] = fmaf(w, blo(v.x), a[0]); a[1] = fmaf(w, bhi(v.x), a[1]);
    a[2] = fmaf(w, blo(v.y), a[2]); a[3] = fmaf(w, bhi(v.y), a[3]);
    a[4] = fmaf(w, blo(v.z), a[4]); a[5] = fmaf(w, bhi(v.z), a[5]);
    a[6] = fmaf(w, blo(v.w), a[6]); a[7] = fmaf(w, bhi(v.w), a[7]);
}
__device__ __forceinline__ float dot8(const float (&q)[8], const uint4& v) {
    float s = q[0] * blo(v.x);
    s = fmaf(q[1], bhi(v.x), s); s = fmaf(q[2], blo(v.y), s); s = fmaf(q[3], bhi(v.y), s);
    s = fmaf(q[4], blo(v.z), s); s = fmaf(q[5], bhi(v.z), s); s = fmaf(q[6], blo(v.w), s); s = fmaf(q[7], bhi(v.w), s);
    return s;
}
__device__ __forceinline__ uint4 pack8(const float (&a)[8], float s) {
    return make_uint4(pack_bf16(a[0] * s, a[1] * s), pack_bf16(a[2] * s, a[3] * s), pack_bf16(a[4] * s, a[5] * s), pack_bf16(a[6] * s, a[7] * s));
}
__device__ __forceinline__ uint32_t hmul2(uint32_t a, uint32_t b) { uint32_t d; asm("mul.rn.bf16x2 %0, %1, %2;" : "=r"(d) : "r"(a), "r"(b)); return d; }
__device__ __forceinline__ uint32_t tile_chunk(uint32_t tile, int r, int c) {
    return tile + (c >> 3) * KB + r * 128 + (((c & 7) ^ (r & 7)) << 4);
}
__device__ __forceinline__ uint32_t wsum4(const uint32_t (&a)[4], uint32_t r0, uint32_t r1, uint32_t r2, uint32_t r3) {
    uint32_t z;
    asm("{\n.reg .b32 t;\nmul.rn.bf16x2 t, %1, %5;\nfma.rn.bf16x2 t, %2, %6, t;\nfma.rn.bf16x2 t, %3, %7, t;\nfma.rn.bf16x2 %0, %4, %8, t;\n}"
        : "=r"(z) : "r"(a[0]), "r"(a[1]), "r"(a[2]), "r"(a[3]), "r"(r0), "r"(r1), "r"(r2), "r"(r3));
    return z;
}
__device__ __forceinline__ void softmax4(const float (&s)[4], const float (&u)[4], int lane, uint32_t (&a)[4]) {
    const bool b = lane & 4, c = lane & 8;
    const float k0 = (b ? u[1] : s[0]) + __shfl_xor_sync(0xffffffffu, b ? s[1] : u[0], 4);
    const float k1 = (b ? u[3] : s[2]) + __shfl_xor_sync(0xffffffffu, b ? s[3] : u[2], 4);
    const float e = (c ? k1 : k0) + __shfl_xor_sync(0xffffffffu, c ? k0 : k1, 9);
    float pe;
    asm("ex2.approx.ftz.f32 %0, %1;" : "=f"(pe) : "f"(e * (0.0625f * 1.4426950408889634f)));
    const int l0 = (lane >> 4) * 18;
    const float p0 = __shfl_sync(0xffffffffu, pe, l0), p1 = __shfl_sync(0xffffffffu, pe, l0 + 9);
    const float p2 = __shfl_sync(0xffffffffu, pe, l0 + 4), p3 = __shfl_sync(0xffffffffu, pe, l0 + 13);
    float inv;
    asm("rcp.approx.ftz.f32 %0, %1;" : "=f"(inv) : "f"(((p0 + p1) + (p2 + p3)) + 1e-9f));
    a[0] = pack_bf16(p0 * inv, p0 * inv); a[1] = pack_bf16(p1 * inv, p1 * inv);
    a[2] = pack_bf16(p2 * inv, p2 * inv); a[3] = pack_bf16(p3 * inv, p3 * inv);
}
__device__ __forceinline__ void attention_chunks(const uint4 (&r)[4][2], uint32_t tile, int node, int lane) {
    const uint32_t qa = tile_chunk(tile, node + (lane >> 4), lane & 15);
    const uint4 q0 = lds128(qa), q1 = lds128(qa + 2 * KB);
    float s[4] = {0.f, 0.f, 0.f, 0.f}, u[4] = {0.f, 0.f, 0.f, 0.f};
    mma16816(s, r[0][0].x, r[1][0].x, r[0][0].y, r[1][0].y, q0.x, q0.y); mma16816(u, r[2][0].x, r[3][0].x, r[2][0].y, r[3][0].y, q0.x, q0.y);
    mma16816(s, r[0][0].z, r[1][0].z, r[0][0].w, r[1][0].w, q0.z, q0.w); mma16816(u, r[2][0].z, r[3][0].z, r[2][0].w, r[3][0].w, q0.z, q0.w);
    mma16816(s, r[0][1].x, r[1][1].x, r[0][1].y, r[1][1].y, q1.x, q1.y); mma16816(u, r[2][1].x, r[3][1].x, r[2][1].y, r[3][1].y, q1.x, q1.y);
    mma16816(s, r[0][1].z, r[1][1].z, r[0][1].w, r[1][1].w, q1.z, q1.w); mma16816(u, r[2][1].z, r[3][1].z, r[2][1].w, r[3][1].w, q1.z, q1.w);
    uint32_t a[4];
    softmax4(s, u, lane, a);
#pragma unroll
    for (int h = 0; h < 2; ++h)
        sts128(qa + h * 2 * KB, make_uint4(wsum4(a, r[0][h].x, r[1][h].x, r[2][h].x, r[3][h].x), wsum4(a, r[0][h].y, r[1][h].y, r[2][h].y, r[3][h].y),
                                           wsum4(a, r[0][h].z, r[1][h].z, r[2][h].z, r[3][h].z), wsum4(a, r[0][h].w, r[1][h].w, r[2][h].w, r[3][h].w)));
}
__device__ __forceinline__ void attention_frags(const uint4 (&r)[2][4], uint32_t tile, int node, int lane) {
    const int nd = node + ((lane >> 2) & 1);
    const uint32_t qa = tile + (lane >> 4) * KB + nd * 128 + (((lane ^ (lane >> 1 & 4) ^ nd) & 7) << 4);
    const uint4 q0 = ldsm4(qa), q1 = ldsm4(qa + 2 * KB);
    float s[4] = {0.f, 0.f, 0.f, 0.f}, u[4] = {0.f, 0.f, 0.f, 0.f};
    mma16816(s, r[0][0].x, r[0][0].y, r[0][0].z, r[0][0].w, q0.x, q0.y); mma16816(u, r[1][0].x, r[1][0].y, r[1][0].z, r[1][0].w, q0.x, q0.y);
    mma16816(s, r[0][1].x, r[0][1].y, r[0][1].z, r[0][1].w, q0.z, q0.w); mma16816(u, r[1][1].x, r[1][1].y, r[1][1].z, r[1][1].w, q0.z, q0.w);
    mma16816(s, r[0][2].x, r[0][2].y, r[0][2].z, r[0][2].w, q1.x, q1.y); mma16816(u, r[1][2].x, r[1][2].y, r[1][2].z, r[1][2].w, q1.x, q1.y);
    mma16816(s, r[0][3].x, r[0][3].y, r[0][3].z, r[0][3].w, q1.z, q1.w); mma16816(u, r[1][3].x, r[1][3].y, r[1][3].z, r[1][3].w, q1.z, q1.w);
    uint32_t a[4];
    softmax4(s, u, lane, a);
#pragma unroll
    for (int h = 0; h < 2; ++h)
        stsm4(qa + h * 2 * KB, wsum4(a, r[0][2 * h].x, r[0][2 * h].y, r[1][2 * h].x, r[1][2 * h].y), wsum4(a, r[0][2 * h].z, r[0][2 * h].w, r[1][2 * h].z, r[1][2 * h].w),
              wsum4(a, r[0][2 * h + 1].x, r[0][2 * h + 1].y, r[1][2 * h + 1].x, r[1][2 * h + 1].y), wsum4(a, r[0][2 * h + 1].z, r[0][2 * h + 1].w, r[1][2 * h + 1].z, r[1][2 * h + 1].w));
}
__device__ __noinline__ void attention_generic(const Params& p, uint32_t tile, int nl, int node, int lane) {
    const uint32_t qa = tile_chunk(tile, nl, lane);
    const uint4 qv = lds128(qa);
    const float q[8] = {blo(qv.x), bhi(qv.x), blo(qv.y), bhi(qv.y), blo(qv.z), bhi(qv.z), blo(qv.w), bhi(qv.w)};
    float z[8] = {0.f, 0.f, 0.f, 0.f, 0.f, 0.f, 0.f, 0.f};
    float den = 0.f;
#pragma unroll 1
    for (int e = 0; e < p.Ee; e += 32) {
        const bool m = (e + lane < p.Ee) && (__ldg(p.edst + e + lane) == node);
        const int sv = m ? __ldg(p.esrc + e + lane) : 0;
        uint32_t bal = __ballot_sync(0xffffffffu, m);
        while (bal) {
            const int l = __ffs(bal) - 1; bal &= bal - 1;
            const uint4 v = ldg_in(row_ptr(p.x + lane * 16, __shfl_sync(0xffffffffu, sv, l)));
            float c = dot8(q, v);
#pragma unroll
            for (int o = 16; o; o >>= 1) c += __shfl_xor_sync(0xffffffffu, c, o);
            const float pe = expf(c * 0.0625f);
            den += pe;
            fma8(z, pe, v);
        }
    }
    sts128(qa, pack8(z, 1.f / (den + 1e-9f)));
}
__device__ __noinline__ void local_generic(const Params& p, int node0, int w, int lane) {
    float a0[8], a1[8], a2[8], a3[8];
#pragma unroll
    for (int k = 0; k < 8; ++k) { a0[k] = 0.f; a1[k] = 0.f; a2[k] = 0.f; a3[k] = 0.f; }
#pragma unroll 1
    for (int e = 0; e < p.E; e += 32) {
        const int dl = (e + lane < p.E) ? __ldg(p.dst + e + lane) - node0 - w : -1;
        const int k = dl == 0 ? 0 : dl == AW ? 1 : dl == 2 * AW ? 2 : (dl == 3 * AW && w + 3 * AW < NPC) ? 3 : -1;
        const int sv = k >= 0 ? __ldg(p.src + e + lane) : 0;
        uint32_t bal = __ballot_sync(0xffffffffu, k >= 0);
        while (bal) {
            const int l = __ffs(bal) - 1; bal &= bal - 1;
            const int s = __shfl_sync(0xffffffffu, sv, l), kk = __shfl_sync(0xffffffffu, k, l);
            const uint4 v = ldg_sc(p.H + lane * N + s);
            if (kk & 2) { if (kk & 1) fma8(a3, 1.f, v); else fma8(a2, 1.f, v); }
            else        { if (kk & 1) fma8(a1, 1.f, v); else fma8(a0, 1.f, v); }
        }
    }
    const int n = node0 + w;
    red_row(p.out + n * 32 + lane, pack8(a0, __bfloat162float(p.dis[n])));
    red_row(p.out + (n + AW) * 32 + lane, pack8(a1, __bfloat162float(p.dis[n + AW])));
    red_row(p.out + (n + 2 * AW) * 32 + lane, pack8(a2, __bfloat162float(p.dis[n + 2 * AW])));
    if (w + 3 * AW < NPC) red_row(p.out + (n + 3 * AW) * 32 + lane, pack8(a3, __bfloat162float(p.dis[n + 3 * AW])));
}
__device__ __forceinline__ uint32_t hadd2(uint32_t a, uint32_t b) { uint32_t d; asm("add.rn.bf16x2 %0, %1, %2;" : "=r"(d) : "r"(a), "r"(b)); return d; }
__device__ __forceinline__ float plo(uint32_t v) { uint32_t d; asm("prmt.b32 %0, %1, 0, 0x1044;" : "=r"(d) : "r"(v)); return __uint_as_float(d); }
template <int HI, int NR>
__device__ __forceinline__ uint32_t agg_sum(uint32_t w, uint32_t base) {
    uint32_t a, r0, r1, r2, r3;
    if (HI) asm("dp2a.hi.u32.u32 %0, %1, %2, %3;" : "=r"(a) : "r"(w), "r"(0x10000010u), "r"(base));
    else    asm("dp2a.lo.u32.u32 %0, %1, %2, %3;" : "=r"(a) : "r"(w), "r"(0x10000010u), "r"(base));
    if (NR == 2) {
        asm volatile("ldmatrix.sync.aligned.m8n8.x2.shared.b16 {%0,%1}, [%2];" : "=r"(r0), "=r"(r1) : "r"(a));
        return hadd2(r0, r1);
    }
    asm volatile("ldmatrix.sync.aligned.m8n8.x4.shared.b16 {%0,%1,%2,%3}, [%4];" : "=r"(r0), "=r"(r1), "=r"(r2), "=r"(r3) : "r"(a));
    return hadd2(hadd2(r0, r1), hadd2(r2, r3));
}
struct Unit { uint4 a, b; };
__device__ __forceinline__ uint32_t unit_stale(const Unit& x, uint32_t lt) {
    return ((x.a.x ^ lt) | (x.b.x ^ lt)) & 0xc000u;
}
__device__ __forceinline__ uint32_t agg_tail(float lo, float hi, uint32_t s, const uint4& w, uint32_t base, uint32_t b5, uint32_t b6) {
    if (b5 > 0xffffu) {
        s = hadd2(s, agg_sum<1, 4>(w.z, base));
        if (b6) {
            const uint32_t u = b6 > 0xffffu ? agg_sum<0, 4>(w.w, base) : agg_sum<0, 2>(w.w, base);
            lo += plo(u); hi += bhi(u);
        }
    } else if (b5) s = hadd2(s, agg_sum<1, 2>(w.z, base));
    const float f = bhi(w.w);
    return pack_bf16((lo + plo(s)) * f, (hi + bhi(s)) * f);
}
__device__ __forceinline__ void agg_unit(const Unit& x, uint32_t base, uint32_t stg, uint32_t lt) {
    const uint32_t s0 = hadd2(agg_sum<0, 4>(x.a.x, base), agg_sum<1, 4>(x.a.x, base)), u0 = hadd2(agg_sum<0, 4>(x.b.x, base), agg_sum<1, 4>(x.b.x, base));
    const uint32_t s1 = hadd2(agg_sum<0, 4>(x.a.y, base), agg_sum<1, 4>(x.a.y, base)), u1 = hadd2(agg_sum<0, 4>(x.b.y, base), agg_sum<1, 4>(x.b.y, base));
    const uint32_t s2 = agg_sum<0, 4>(x.a.z, base), u2 = agg_sum<0, 4>(x.b.z, base);
    const uint32_t a5 = __ballot_sync(0xffffffffu, x.a.z > (lt | 0xffffu)), a6 = __ballot_sync(0xffffffffu, x.a.w & 0x3fffu);
    const uint32_t b5 = __ballot_sync(0xffffffffu, x.b.z > (lt | 0xffffu)), b6 = __ballot_sync(0xffffffffu, x.b.w & 0x3fffu);
    const uint32_t oa = agg_tail(plo(s0) + plo(s1), bhi(s0) + bhi(s1), s2, x.a, base, a5, a6);
    const uint32_t ob = agg_tail(plo(u0) + plo(u1), bhi(u0) + bhi(u1), u2, x.b, base, b5, b6);
    asm volatile("stmatrix.sync.aligned.m8n8.x2.shared.b16 [%0], {%1,%2};" :: "r"(stg), "r"(oa), "r"(ob) : "memory");
}

__global__ void __launch_bounds__(NTHR, 1)
fused_kernel(const __grid_constant__ Params p,
             const __grid_constant__ CUtensorMap tmX, const __grid_constant__ CUtensorMap tmWl,
             const __grid_constant__ CUtensorMap tmM, const __grid_constant__ CUtensorMap tmWv,
             const __grid_constant__ CUtensorMap tmR, const __grid_constant__ CUtensorMap tmO,
             const __grid_constant__ CUtensorMap tmG, const __grid_constant__ CUtensorMap tmQ,
             const __grid_constant__ CUtensorMap tmK, const __grid_constant__ CUtensorMap tmV3)
{
    extern __shared__ __align__(1024) unsigned char smem[];
    constexpr uint32_t sb = 1024;
    const int tid = threadIdx.x, lane = tid & 31;
    const int warp = __shfl_sync(0xffffffffu, tid >> 5, 0);
    const int cta = blockIdx.x;
    const int node0 = cta * NPC;
    const bool rowcta = cta < RCTA;
    const int slice = cta >> 2, quarter = cta & 3;
    const int nlast = 12 + (quarter == 3);
    const int i0 = (cta >> 3) * 16, j0 = (cta & 7) * 32;
    constexpr uint32_t bars = sb + SM_MISC, sS = sb + SM_S, sT = sb + SM_T;

    const bool stage = rowcta && p.edst4;
    auto slow_cta = [&]() { uint32_t a, b; asm volatile("ld.shared.v2.u32 {%0, %1}, [%2];" : "=r"(a), "=r"(b) : "r"(bars + MI_SLOW) : "memory"); return a || b > OVCAP; };
    auto publish = [&](int set) {
        const uint4 dv = lds128(bars + MI_DIS + set * 16);
        uint4 v = lds128(sb + X_IMG + set * 512 + lane * 16);
        const uint4 z = lds128(sb + X_DEF + set * 64 + (lane & 3) * 16);
        if ((lane & 3) == 3) { v.x = __byte_perm(v.x, v.y, 0x5410); v.y = v.w; }
        v.x = __vmaxu2(v.x, z.x); v.y = __vmaxu2(v.y, z.y); v.z = __vmaxu2(v.z, z.z); v.w = __vmaxu2(v.w, z.w);
        if (slow_cta()) v = make_uint4(0, 0, 0, 0);
        const uint32_t lt = list_tag(lds32(bars + MI_EPOCH));
        v.x |= lt; v.y |= lt; v.z |= lt; v.w |= lt;
        if ((lane & 3) == 3) { const uint32_t sel = lane & 16 ? 0x7632 : 0x5410; v.z = __byte_perm(dv.x, dv.y, sel); v.w = __byte_perm(dv.z, dv.w, sel); }
        uint32_t* ip = (uint32_t*)p.idx + (cta * 10 + set) * 128 + lane;
        st_relaxed(ip, __byte_perm(v.x, v.z, 0x5410));      st_relaxed(ip + 32, __byte_perm(v.x, v.z, 0x7632));
        st_relaxed(ip + 64, __byte_perm(v.y, v.w, 0x5410)); st_relaxed(ip + 96, __byte_perm(v.y, v.w, 0x7632));
    };

    if (warp >= AW) {
        const int pw = warp - AW;
        auto init = [&](int b0, int b1, int c) {
#pragma unroll
            for (int b = b0; b < b1; b += 8) mbar_init(bars + b, c);
        };
        uint4 pe = make_uint4(0, 0, 0, 0);
        if (pw == 0) {
            if (elect()) {
                PROF(0);
                prefetch_map(&tmQ); prefetch_map(&tmK); prefetch_map(&tmX); prefetch_map(&tmWl);
                init(B_K, B_A, 1);
                asm volatile("fence.mbarrier_init.release.cluster;" ::: "memory");
                mbar_expect(bars + B_QK, 3 * UNIT);
                tma3d(sS + A3 * UNIT, &tmQ, i0, bars + B_QK);
                tma3d(sS + (A3 + 1) * UNIT, &tmK, j0, bars + B_QK);
            }
        } else {
            if (elect()) {
                if (pw & 2) {
                    if (pw & 1) { init(B_GO, B_Z, 1); init(B_RND, B_RND + 96, 12); mbar_init(bars + B_RND + 96, nlast); }
                    else        { init(B_F, B_GO, GW); init(B_FA, B_SENT, 8); mbar_init(bars + B_SENT, LW + 4); }
                } else          { init(B_A, B_F, 4); mbar_init(bars + B_S, 6); mbar_init(bars + B_VE, GW); mbar_init(bars + B_Z, AW); init(B_HV, B_RV + 8, 1); }
                asm volatile("fence.mbarrier_init.release.cluster;" ::: "memory");
            }
        }
        bar_arrive(4, LT + 128);
        bar_arrive(0, GT + 128);
        if (pw == 0 && rowcta && elect()) {
#pragma unroll
            for (int kq = 0; kq < 4; ++kq) mbar_expect(bars + B_K + kq * 8, KB + 4 * UNIT);
#pragma unroll
            for (int i = 7; i >= 0; --i) {
                const int kq = (XORD >> (4 * i)) & 3;
                if ((XORD >> (4 * i)) & 4) tma3d(sS + (kq == 3 ? A4 : 4 * kq) * UNIT, &tmWl, kq * 64, bars + B_K + kq * 8);
                else tma2d(sT + kq * KB, &tmX, kq * 64, node0, bars + B_K + kq * 8);
            }
            PROF(3);
            prefetch_map(&tmM); prefetch_map(&tmG); prefetch_map(&tmWv); prefetch_map(&tmV3); prefetch_map(&tmR);
        }
        if (pw >= 2 ? stage : pw && rowcta && lane < 10) pe = ldg_in(pw >= 2 ? (const char*)(p.esrc + (node0 + 32 * (pw - 2) + lane) * 4) : (const char*)(p.dis + node0 + lane * 8));
        auto load_units = [&](const CUtensorMap* tm, int kq, int slot) {
            if (elect()) { mbar_expect(bars + B_K + kq * 8, 4 * UNIT); tma3d(sS + slot * UNIT, tm, kq * 64, bars + B_K + kq * 8); }
        };
        const int v0 = pw ? pw - 2 : 2;
        auto tile_rows = [&](uint2 (&e)[6], int c) {
#pragma unroll
            for (int n = 0; n < 6; ++n) {
                const int v = min(v0 + 3 * n, 15);
                asm volatile("ld.shared.v2.u32 {%0, %1}, [%2];" : "=r"(e[n].x), "=r"(e[n].y) : "r"(bars + MI_ES + ((v >> 2) * 16 + c * 4 + (v & 3)) * 8) : "memory");
            }
        };
        auto stage_tiles = [&](const uint2 (&e)[6], int c) {
            mbar_wait(bars + (c ? B_F + 32 + c * 8 : B_CGO), 0);
            if (elect()) {
#pragma unroll
                for (int n = 0; n < 6; ++n) {
                    const int v = v0 + 3 * n;
                    if (n < 5 || v < 16) {
                        const uint32_t dst = sS + (A_TILES >> (8 * c) & 255) * UNIT + v * 2048, bar = bars + B_A + ((v & 12) + c) * 8;
                        mbar_expect(bar, 2048);
                        tma2d(dst, &tmG, 0, e[n].x & 0xffffu, bar);        tma2d(dst + 512, &tmG, 0, e[n].x >> 16, bar);
                        tma2d(dst + 1024, &tmG, 0, e[n].y & 0xffffu, bar); tma2d(dst + 1536, &tmG, 0, e[n].y >> 16, bar);
                    }
                }
            }
            if (pw == 2 && lane == 0) PROF(45 + c);
        };
        if (pw >= 2) asm volatile("st.shared.v2.u32 [%0], {%1, %2};" :: "r"(bars + MI_ES + ((pw - 2) * 32 + lane) * 8), "r"(pe.x | pe.y << 16), "r"(pe.z | pe.w << 16) : "memory");
        else if (pw == 1 && lane < 10) sts128(bars + MI_DIS + lane * 16, pe);
        {
            bar_sync(1, GT + 128);
            const int v = tid - AW * 32;
            const uint32_t rp = sb + SM_X + ((v >> 3) * 32 + (((v & 7) * 4 + (v & 24)) & 31)) * 4;
            const float4 v0 = lds128f(rp), v1 = lds128f(rp + 2048), v2 = lds128f(rp + 4096), v3 = lds128f(rp + 6144);
            p.M[(i0 + (v >> 3)) * 64 + (j0 >> 2) + (v & 7)] =
                make_uint2(pack_bf16((v0.x + v1.x) + (v2.x + v3.x), (v0.y + v1.y) + (v2.y + v3.y)),
                           pack_bf16((v0.z + v1.z) + (v2.z + v3.z), (v0.w + v1.w) + (v2.w + v3.w)));
            warp_arrive(bars + B_SENT);
        }
        if (pw != 1 && rowcta) {
            uint2 e[3][6];
#pragma unroll
            for (int c = 0; c < 3; ++c) tile_rows(e[c], c);
            mbar_wait(bars + B_EPO, 0);
            mbar_wait(bars + B_F, 0);
#pragma unroll 1
            for (int c = 0; c < 3; ++c) {
                if (pw == 0 && c == 0) {
                    mbar_wait(bars + B_CGO, 0);
                    wait_count(p.sync + SY_M, (lds32(bars + MI_EPOCH) + 1) * NCTA);
                    fence_async_gmem();
                    if (lane == 0) PROF(2);
                    load_units(&tmM, 0, A0);
                    if (lane == 0) PROF(39);
                    mbar_wait(bars + B_F + 8, 0);  load_units(&tmM, 1, A1);
                    mbar_wait(bars + B_F + 16, 0); load_units(&tmM, 2, A2);
                    warp_arrive(bars + B_MI);
                    if (lane == 0) PROF(40);
                }
                if (pw == 0 && c == 1) { mbar_wait(bars + B_F + 32, 0); load_units(&tmM, 3, A0); }
                if (stage) stage_tiles(e[0], c);
#pragma unroll
                for (int n = 0; n < 6; ++n) { e[0][n] = e[1][n]; e[1][n] = e[2][n]; }
            }
        }
        if (pw == 0) {
            if (rowcta) {
                mbar_wait(bars + B_FA, 0); mbar_wait(bars + B_FA + 8, 0); fence_async_smem();
                mbar_wait(bars + B_HR, 0);
                if (elect()) {
                    mbar_expect(bars + B_K, 4 * UNIT);     tma3d(sS + A3 * UNIT, &tmWv, 0, bars + B_K);
                    mbar_expect(bars + B_K + 8, 4 * UNIT); tma3d(sS + A1 * UNIT, &tmWv, 64, bars + B_K + 8);
                }
                mbar_wait(bars + B_FA + 16, 0); fence_async_smem();  load_units(&tmWv, 2, A2);
                mbar_wait(bars + B_XF, 0);      fence_async_smem();
                if (elect()) {
                    mbar_expect(bars + B_K + 24, 4 * UNIT);
#pragma unroll
                    for (int ks = 0; ks < 4; ++ks) tma3d(sS + (A5 + ks) * UNIT, &tmV3, 192 + ks * 16, bars + B_K + 24);
                }
                if (lane == 0) PROF(5);
            }
        } else if (pw == 1) {
            mbar_wait(bars + B_SENT, 0);
            if (elect()) { PROF(38); red_release(p.sync + SY_M); PROF(1); mbar_arrive(bars + B_CGO); }
            if (lane < 8) asm volatile("prefetch.global.L2 [%0];" :: "l"(p.wv + (cta * 8 + lane) * 128));
            mbar_wait(bars + B_EPO, 0);
            if (rowcta) {
                mbar_wait(bars + B_HS, 0);
                mbar_wait(bars + B_LF, 0);
                fence_async_smem();
                mbar_wait(bars + B_MI, 0);
                mbar_wait(bars + B_K, 1);
                uint32_t tn = clk();
#pragma unroll 1
                for (int s = 0; s < 32; s += 2) {
                    wait_clk(tn); tn += HPER;
                    if (elect()) {
                        bulk_store(p.H + s * N + node0, sS + A4 * UNIT + s * 1280, 1280);
                        bulk_store(p.H + (s + 1) * N + node0, sS + A4 * UNIT + s * 1280 + 1280, 1280);
                    }
                }
#pragma unroll 1
                for (int z = cta; z < ER * AW * 16; z += RCTA) {
                    wait_clk(tn); tn += HPER;
                    if (elect()) bulk_store(p.out + ((z & 3) * (UPQ * 16) + (z >> 2) * 4) * 32, sb + X_ZERO, 2048);
                }
                if (elect()) {
                    bulk_commit();
                    asm volatile("cp.async.bulk.wait_group 0;" ::: "memory");
                    PROF(43);
                    fence_async_gmem();
                    red_release(p.sync + SY_H);
                    mbar_arrive(bars + B_HR);
                    PROF(31);
                }
            }
            const uint32_t target = (lds32(bars + MI_EPOCH) + 1) * RCTA;
            if (rowcta) mbar_wait(bars + B_FA + 24, 0);
            if (lane < 8) sts128(sS + lane * 16, make_uint4(0, 0, 0, 0));
            fence_async_smem();
            wait_count(p.sync + SY_H, target);
            fence_async_gmem();
            if (lane == 0) PROF(6);
            const char* hs = (const char*)(p.H + slice * N) - 128;
            auto chunk = [&](int lo, int hi) { mbar_expect(bars + B_S, hi - lo); bulk_load(sS + lo, hs + lo, hi - lo, bars + B_S); };
            if (elect()) { chunk(A4 * UNIT, A5 * UNIT); chunk(128, 4 * UNIT); mbar_arrive(bars + B_HV); }
            if (rowcta) mbar_wait(bars + B_F + 64, 0);
            if (elect()) chunk(A3 * UNIT, (A3 + 4) * UNIT);
            if (rowcta) mbar_wait(bars + B_F + 72, 0);
            if (elect()) chunk(A1 * UNIT, (A1 + 4) * UNIT);
            if (rowcta) mbar_wait(bars + B_F + 80, 0);
            if (elect()) chunk(A2 * UNIT, (A2 + 4) * UNIT);
            if (rowcta) mbar_wait(bars + B_F + 88, 0);
            if (elect()) chunk(A5 * UNIT, SLICE_END);
            if (lane == 0) PROF(7);
        } else {
            mbar_wait(bars + B_EPO, 0);
            const uint32_t epoch1 = lds32(bars + MI_EPOCH) + 1;
            if (pw == 2) {
                if (rowcta) {
                    uint32_t early = 0;
#pragma unroll
                    for (int r = 0; r < 5; ++r) { const int u = cta * 5 + r; early |= (u - min(u / UPQ, 3) * UPQ < ER * AW) << r; }
                    auto put_r = [&](bool add) {
#pragma unroll 1
                        for (int r = 0; r < 5; ++r) {
                            const int u = cta * 5 + r;
                            if ((early >> r & 1) == add) {
                                if (elect()) {
#pragma unroll
                                    for (int kb = 0; kb < 4; ++kb) {
                                        if (add) tma2d_add(&tmR, sT + kb * KB + r * 2048, kb * 64, u * 16);
                                        else     tma2d_store(&tmR, sT + kb * KB + r * 2048, kb * 64, u * 16);
                                    }
                                }
                            }
                        }
                        bulk_commit();
                    };
                    mbar_wait(bars + B_R, 0);
                    fence_async_smem();
                    put_r(false);
                    if (elect()) {
                        asm volatile("cp.async.bulk.wait_group 0;" ::: "memory");
                        fence_async_gmem();
                        p.sync[SY_SLOW + cta] = slow_cta();
                        red_release(p.sync + SY_R);
                        PROF(22);
                    }
                    mbar_wait(bars + B_S, 0);
                    put_r(true);
                    bulk_wait_read<0>();
                    if (lane == 0) PROF(41);
                }
                warp_arrive(bars + B_TF);
                wait_count(p.sync + SY_R, epoch1 * RCTA);
                fence_async_gmem();
                warp_arrive(bars + B_RV);
                if (lane == 0) PROF(23);
            } else {
                if (s32(smem) != sb) __trap();
                if (lane == 0) prefetch_map(&tmO);
                mbar_wait(bars + B_XF, 0);
                if (elect()) red_relaxed(p.sync + SY_L);
                wait_count(p.sync + SY_L, epoch1 * NCTA);
                warp_arrive(bars + B_GO);
                if (lane == 0) PROF(42);
                if (cta == 0 && lane < 16) *(volatile uint32_t*)(p.sync + lane * 32) = epoch1;
#pragma unroll 1
                for (int i = 0; i < 13; ++i) {
                    if (i == 2 * ER) mbar_wait(bars + B_RV, 0);
                    mbar_wait(bars + B_RND + i * 8, 0);
                    fence_async_smem();
                    if (elect()) {
                        tma2d_add(&tmO, sb + SM_X + i * 3072, slice * 8, quarter * (UPQ * 16) + i * 192);
                        if (i == 12 && quarter == 3) tma2d_add(&tmO, sb + SM_X + 13 * 3072, slice * 8, 3 * (UPQ * 16) + 13 * 192);
                    }
                    if (lane == 0 && !(i & 1)) PROF(53 + (i >> 1));
                }
                bulk_commit();
                if (lane == 0) PROF(8);
                bulk_wait_read<0>();
                if (lane == 0) PROF(9);
            }
        }
        if (pw < 2) {
            mbar_wait(bars + B_EPO, 0);
            mbar_wait(bars + B_XF, 0);
            const int novf = min(lds32(bars + MI_NOVF), (uint32_t)OVCAP);
#pragma unroll 1
            for (int o = OB * pw; o < novf; o += 2 * OB) {
                const int n = min(novf - o, OB);
                uint32_t w = lds32(bars + MI_OVF + (o + min(lane, n - 1)) * 4);
                int rk = 0;
#pragma unroll 1
                for (int j = 0; j < n; ++j) { const uint32_t y = __shfl_sync(0xffffffffu, w, j); rk += y < w || (y == w && j < lane); }
                if (lane < n) sts32(bars + MI_OVF + (o + rk) * 4, w);
                __syncwarp();
                w = lds32(bars + MI_OVF + (o + min(lane, n - 1)) * 4);
                const uint32_t more = __ballot_sync(0xffffffffu, (((__shfl_down_sync(0xffffffffu, w, 1) ^ w) >> 14) == 0) & (lane + 1 < n));
                const uint32_t f = __ldg((const unsigned short*)p.dis + (w >> 14)) * 0x10001u;
                mbar_wait(bars + B_HV, 0);
                uint4 v[OB];
#pragma unroll
                for (int i = 0; i < OB; i += 3) {
                    if (i < n) {
#pragma unroll
                        for (int j = i; j < i + 3; ++j) {
                            const uint32_t s = __shfl_sync(0xffffffffu, w, j) & 0x3fffu;
                            v[j] = make_uint4(0, 0, 0, 0);
                            if (j < n) v[j] = ldg_sc(p.H + lane * N + s);
                        }
#pragma unroll
                        for (int j = i; j < i + 3; ++j) {
                            const uint32_t fj = __shfl_sync(0xffffffffu, f, j);
                            v[j] = make_uint4(hmul2(v[j].x, fj), hmul2(v[j].y, fj), hmul2(v[j].z, fj), hmul2(v[j].w, fj));
                            if (j && (more >> (j - 1) & 1)) v[j] = make_uint4(hadd2(v[j].x, v[j - 1].x), hadd2(v[j].y, v[j - 1].y), hadd2(v[j].z, v[j - 1].z), hadd2(v[j].w, v[j - 1].w));
                        }
                    }
                }
                mbar_wait(bars + B_RV, 0);
                const uint32_t go = __ballot_sync(0xffffffffu, lane < n && !ld_relaxed(p.sync + SY_SLOW + (w >> 14) / NPC)) & ~more;
#pragma unroll
                for (int j = 0; j < OB; ++j)
                    if (go >> j & 1) red_row(p.out + (__shfl_sync(0xffffffffu, w, j) >> 14) * 32 + lane, v[j]);
            }
            if (lane == 0) PROF(pw ? 48 : 44);
        }
    } else {
        const int g = lane >> 2, t = lane & 3;
        const int wi = warp < GW ? warp + LW : warp - GW;
        if (warp < GW) {
            const int wg = warp >> 2, w4 = warp & 3;
            uint32_t h[20];
            sts32(bars + MI_TOUCH, (uint32_t)(uint64_t)p.dis ^ p.Ee);
            if (rowcta) {
#pragma unroll
                for (int j = 0; j < 10; ++j) h[j] = __ldg((const uint32_t*)p.dis + (node0 >> 1) + 4 * j + t);
            }
            bar_sync(0, GT + 128);
            {
                const int cw = (w4 - wg * (MW == 1 ? 1 : MW == 2 ? 2 : 0)) & 3;
                if (cw < MW) {
                    const uint32_t qa = sS + A3 * UNIT + wg * 2048 + (lane & 15) * 128 + (((lane >> 4) ^ (lane & 7)) << 4);
                    const uint32_t ka = sS + (A3 + 1) * UNIT + wg * 4096 + (cw * (32 / MW) + (lane & 7)) * 128 + (((lane >> 3) ^ (lane & 7)) << 4);
                    mbar_wait(bars + B_QK, 0);
                    __syncwarp();
                    if (tid == 0) PROF(33);
                    const uint4 a0 = ldsm4(qa), a1 = ldsm4(qa ^ 32), a2 = ldsm4(qa ^ 64), a3 = ldsm4(qa ^ 96);
                    uint4 bb[4 / MW][2];
#pragma unroll
                    for (int nb = 0; nb < 4 / MW; ++nb) { bb[nb][0] = ldsm4(ka + nb * 1024); bb[nb][1] = ldsm4((ka ^ 64) + nb * 1024); }
#pragma unroll
                    for (int nb = 0; nb < 4 / MW; ++nb) {
                        const uint4 b0 = bb[nb][0], b1 = bb[nb][1];
                        float c[4] = {0.f, 0.f, 0.f, 0.f}, e[4] = {0.f, 0.f, 0.f, 0.f};
                        mma16816(c, a0.x, a0.y, a0.z, a0.w, b0.x, b0.y); mma16816(e, a1.x, a1.y, a1.z, a1.w, b0.z, b0.w);
                        mma16816(c, a2.x, a2.y, a2.z, a2.w, b1.x, b1.y); mma16816(e, a3.x, a3.y, a3.z, a3.w, b1.z, b1.w);
                        const uint32_t rp = sb + SM_X + ((wg * 16 + g) * 32 + (((cw * (4 / MW) + nb + g) & 3) * 8) + 2 * t) * 4;
                        sts64(rp, __float_as_uint(c[0] + e[0]), __float_as_uint(c[1] + e[1]));
                        sts64(rp + 1024, __float_as_uint(c[2] + e[2]), __float_as_uint(c[3] + e[3]));
                    }
                }
                bar_arrive(1, GT + 128);
            }
            if (rowcta) {
                float d[40];
                const uint32_t uw = sS + wg * UNIT, fb = bars + B_F;
                fence_async_smem();
                mbar_wait(bars + B_SENT, 0);
                if (tid == 0) PROF(35);
                gemm_quarter<0>(d, uw + A0 * UNIT, sT, bars + B_K, 0);
                if (tid == 0) PROF(10);
                gemm_quarter<1>(d, uw + A1 * UNIT, sT, bars + B_K, 0, fb);
                gemm_quarter<2>(d, uw + A2 * UNIT, sT, bars + B_K, 0, fb + 8);
                gemm_quarter<3>(d, uw + A4 * UNIT, sT, bars + B_K, 0, fb + 16);
                wg_wait<0>(); warp_arrive(fb + 24);
                if (tid == 0) PROF(11);
#pragma unroll
                for (int j = 9; j >= 0; --j) {
                    const float s0 = blo(h[j]), s1 = bhi(h[j]);
                    h[2 * j + 1] = pack_bf16(d[4 * j + 2] * s0, d[4 * j + 3] * s1);
                    h[2 * j]     = pack_bf16(d[4 * j] * s0, d[4 * j + 1] * s1);
                }
                mbar_wait(fb + 24, 0);
                __syncwarp();
                {
                    const uint32_t sa = sS + A4 * UNIT + warp * 2560 + (lane & 8) * 160 + (lane >> 4) * 128 + (lane & 7) * 16;
#pragma unroll
                    for (int i = 0; i < 5; ++i) stsm4t(sa + i * 256, h[4 * i], h[4 * i + 1], h[4 * i + 2], h[4 * i + 3]);
                }
                warp_arrive(bars + B_HS);
                if (tid == 0) PROF(60);
                uint4 e3 = make_uint4(0, 0, 0, 0);
                if (stage) e3 = ldg_in(p.esrc + (node0 + 16 * wg + 12 + w4) * 4);
                gemm_quarter<0>(d, uw + A0 * UNIT, sT, bars + B_K, 1);
                if (tid == 0) PROF(12);
                gemm_quarter<1>(d, uw + A1 * UNIT, sT, bars + B_K, 1, fb + 32);
                gemm_quarter<2>(d, uw + A2 * UNIT, sT, bars + B_K, 1, fb + 40);
                mbar_wait(bars + B_LF, 0);
                const uint32_t ebad = lds32(bars + MI_EBAD);
                gemm_quarter<3>(d, uw + A0 * UNIT, sT, bars + B_K, 1, fb + 48);
                if (tid == 0) PROF(13);
                wg_wait<0>(); warp_arrive(fb + 56);
                if (tid == 0) PROF(14);
                pack_acc(h, d);
                mbar_wait(fb + 32 + wg * 8, 0);
                __syncwarp();
                store_tile(h, sT, wg, w4, lane);
                warp_arrive(bars + B_Q);
                auto stage3 = [&]() {
                    mbar_wait(fb + 56, 0);
                    if (stage && elect()) {
                        const uint32_t dst = uw + A0 * UNIT + w4 * 2048, bar = bars + B_A + (4 * wg + 3) * 8;
                        mbar_expect(bar, 2048);
                        tma2d(dst, &tmG, 0, e3.x, bar);        tma2d(dst + 512, &tmG, 0, e3.y, bar);
                        tma2d(dst + 1024, &tmG, 0, e3.z, bar); tma2d(dst + 1536, &tmG, 0, e3.w, bar);
                    }
                };
                const uint32_t rows = uw + (w4 & 1) * 4096 + (lane & 4) * 512 + (lane & 8) * 64 + (((lane ^ (lane >> 2 & 4)) & 7) << 4);
#pragma unroll 1
                for (int c2 = 0; c2 < 4; c2 += 2) {
                    const int c = (w4 >> 1) + c2;
                    const int n = 16 * wg + 4 * c + 2 * (w4 & 1);
                    if (stage) mbar_wait(bars + B_A + (4 * wg + c) * 8, 0);
                    if (tid == 0) PROF(c ? 50 : 15);
                    if (tid == 96) PROF(c == 1 ? 51 : 52);
                    if (!ebad) {
                        const uint32_t ra = rows + (A_TILES >> (8 * c) & 255) * UNIT;
                        uint4 r[2][4];
#pragma unroll
                        for (int kb = 0; kb < 4; ++kb) { r[0][kb] = ldsm4(ra + kb * 128); r[1][kb] = ldsm4(ra + 1024 + kb * 128); }
                        warp_arrive(bars + B_FA + c * 8);
                        if (c2 == 0) { stage3(); mbar_wait(bars + B_Q, 0); }
                        __syncwarp();
                        attention_frags(r, sT, n, lane);
                    } else {
                        warp_arrive(bars + B_FA + c * 8);
                        if (c < 2) stage3();
                        mbar_wait(bars + B_Q, 0);
                        attention_generic(p, sT, n, node0 + n, lane); attention_generic(p, sT, n + 1, node0 + n + 1, lane);
                    }
                }
                fence_async_smem();
                warp_arrive(bars + B_Z);
                if (tid == 0) PROF(16);
                mbar_wait(bars + B_K, 0);
                if (tid == 0) PROF(17);
                gemm_quarter<0>(d, uw + A3 * UNIT, sT, bars + B_Z, 0);
                gemm_quarter<1>(d, uw + A1 * UNIT, sT, bars + B_K, 0, fb + 64);
                gemm_quarter<2>(d, uw + A2 * UNIT, sT, bars + B_K, 0, fb + 72);
                {
                    mbar_wait(bars + B_K + 24, 0);
                    __syncwarp();
                    const uint32_t a = desc_lo(sS + A5 * UNIT + wg * 2048), b = desc_lo(sT) + ((3 * KB) >> 4);
                    wg_fence();
                    wgmma80<false>(d, a, b);            wg_commit(); wg_wait<1>(); warp_arrive(fb + 80);
                    wgmma80<false>(d, a + 512, b + 2);  wg_commit(); wg_wait<1>(); warp_arrive(fb + 88);
                    wgmma80<false>(d, a + 1024, b + 4);
                    wgmma80<false>(d, a + 1536, b + 6); wg_commit();
                }
                wg_wait<0>(); warp_arrive(bars + B_VE);
                if (tid == 0) PROF(18);
                pack_acc(h, d);
                mbar_wait(wg == 3 ? bars + B_VE : fb + 64 + wg * 8, 0);
                __syncwarp();
                store_tile(h, sT, wg, w4, lane);
                warp_arrive(bars + B_R);
                if (tid == 0) PROF(19);
            }
        } else {
            const int lw = warp - GW, tl = tid - GT;
            uint32_t dd[5], ss[5];
            const int e0 = cta * p.chunk;
            {
                const int last = max(p.Efast - 2, 0);
                const uint32_t ea = min(e0 + 2 * tl, last), eb = min(e0 + 2 * tl + 2 * LT, last), ec = min(e0 + tl + 4 * LT, last + 1);
                const int2 d0 = __ldg((const int2*)(p.dst + ea)), d1 = __ldg((const int2*)(p.dst + eb));
                dd[4] = __ldg(p.dst + ec);
                const int2 s0 = __ldg((const int2*)(p.src + ea)), s1 = __ldg((const int2*)(p.src + eb));
                ss[4] = __ldg(p.src + ec);
                dd[0] = d0.x; dd[1] = d0.y; dd[2] = d1.x; dd[3] = d1.y; ss[0] = s0.x; ss[1] = s0.y; ss[2] = s1.x; ss[3] = s1.y;
            }
            const uint32_t epoch = ld_relaxed(p.sync + (cta & 15) * 32);
            int4 ed = make_int4(0, 0, 0, 0), es = make_int4(0, 0, 0, 0);
            if (stage) {
                ed = __ldg((const int4*)p.edst4 + (uint32_t)(node0 + min(tl, NPC - 1)));
                es = __ldg((const int4*)p.esrc + (uint32_t)(node0 + 64 + (tl >> 4)));
            }
            {
                const uint32_t lo = (tl & 3) * 0x40004000u, hi = (NPC * 2 + (cta & 7)) * 0x010101u;
#pragma unroll
                for (int r = 0; r < 2; ++r) {
                    sts128(sb + X_OUT + (tl + r * LT) * 16, make_uint4(lo, lo, (lo & 0xffffu) | hi << 16, hi));
                    sts128(sb + X_IMG + (tl + r * LT) * 16, make_uint4(0, 0, 0, 0));
                }
            }
            if (tl < 32) sts128(bars + MI_PCNT + tl * 16, make_uint4(0, 0, 0, 0));
            if (tl == 32) { sts32(bars + MI_SLOW, p.chunk == 0); sts32(bars + MI_EBAD, !p.edst4); sts32(bars + MI_NOVF, 0); sts32(bars + MI_FLAGS, 0); }
            bar_sync(2, LT);
            if (tl == 0) PROF(34);
            const int zero = lds32(bars + MI_PCNT + 127 * 4);
            const int ne = min(p.chunk, p.Efast - e0) + zero;
            uint32_t q[5], nx = 0, ox = 0;
            {
                uint32_t c[5];
#pragma unroll
                for (int k = 0; k < 5; ++k) {
                    dd[k] = (k < 4 ? 2 * tl + (k >> 1) * 2 * LT : tl + 4 * LT) < ne ? dd[k] : (RCTA + (lane & 1)) * NPC;
                    c[k] = dd[k] / NPC;
                    q[k] = atoms_add(bars + MI_PCNT + c[k] * 4, c[k] < RCTA);
                }
                if (tl == 0) PROF(36);
#pragma unroll
                for (int k = 0; k < 5; ++k) {
                    const uint32_t w = (((dd[k] - c[k] * NPC) * 8 + (ss[k] & 7u)) << 14) + ss[k] + 8;
                    uint32_t sl = (q[k] >> 2) + ((c[k] >> 3) & 3u);
                    sl = min(sl, sl - 5);
                    const uint32_t ca = sb + X_OUT + c[k] * 64 + ((q[k] + (c[k] >> 1)) & 3u) * 16 + sl;
                    if (q[k] < CELLN) { sts16(ca + sl, w); asm volatile("st.shared.u8 [%0 + 10], %1;" :: "r"(ca), "r"(w >> 16) : "memory"); }
                    nx += q[k] >= CELLN;
                }
                if (nx) ox = atoms_add(bars + MI_NOVF, nx);
                const int nz = node0 + tl + zero;
                if (stage && tl < NPC && ((ed.x != nz) | (ed.y != nz) | (ed.z != nz) | (ed.w != nz))) sts32(bars + MI_FLAGS, W_EBAD);
            }
            if (tl == 0) PROF(37);
            bar_sync(4, LT + 128);
            if (tl == 0) PROF(24);
            const uint32_t tag = ((epoch + zero) % 31u + 1u) << 27;
            {
                const uint32_t fl = lds32(bars + MI_FLAGS) | tag | (lds32(bars + MI_NOVF) > OVCAP / 2 ? W_OVF : 0u);
                uint4* const gp = p.cells + ((tl >> 2) * NCTA + cta) * 4 + (tl & 3);
#pragma unroll
                for (int r = 0; r < 2; ++r) {
                    uint4 w = lds128(sb + X_OUT + (tl + r * LT) * 16);
                    w.w |= fl;
                    if (r == 0 || tl + LT < RCTA * 4) gp[r * (LT / 4) * NCTA * 4] = w;
                }
            }
            warp_arrive(bars + B_SENT);
            if (tl == 0) { sts32(bars + MI_EPOCH, epoch); mbar_arrive(bars + B_EPO); }
            if (tl == 0) PROF(25);
#pragma unroll
            for (int k = 0; k < 5; ++k) {
                if (q[k] >= CELLN) sts32(bars + MI_OVF + min(ox, (uint32_t)OVCAP - 1) * 4, dd[k] << 14 | ss[k]);
                ox += q[k] >= CELLN;
            }
            uint4 r[4][2];
            auto load_rows = [&]() {
                if (stage) {
                    const char* xl = p.x + (lane & 15) * 16;
                    const char* r0 = row_ptr(xl, es.x); const char* r1 = row_ptr(xl, es.y); const char* r2 = row_ptr(xl, es.z); const char* r3 = row_ptr(xl, es.w);
                    r[0][0] = ldg_in(r0); r[0][1] = ldg_in(r0 + 256); r[1][0] = ldg_in(r1); r[1][1] = ldg_in(r1 + 256);
                    r[2][0] = ldg_in(r2); r[2][1] = ldg_in(r2 + 256); r[3][0] = ldg_in(r3); r[3][1] = ldg_in(r3 + 256);
                }
            };
            auto attend = [&]() {
                mbar_wait(bars + B_Q, 0);
                __syncwarp();
                if (!lds32(bars + MI_EBAD)) attention_chunks(r, sT, 64 + 2 * lw, lane);
                else { attention_generic(p, sT, 64 + 2 * lw, node0 + 64 + 2 * lw, lane); attention_generic(p, sT, 65 + 2 * lw, node0 + 65 + 2 * lw, lane); }
                fence_async_smem();
                warp_arrive(bars + B_Z);
                if (tl == 0) PROF(32);
            };
            if (rowcta) {
                mbar_wait(bars + B_SENT, 0);
                if (tl == LT - 1) sts32(sb + X_TAB + NPC * 64, 64);
                if (tl < 128) sts128(sb + X_ZERO + tl * 16, make_uint4(0, 0, 0, 0));
                uint4 c0, c1;
                const uint4* cp = p.cells + cta * (NCTA * 4) + tl;
                mbar_wait(bars + B_CGO, 0);
#pragma unroll 1
                for (int it = 0;; ++it) {
                    c0 = ld_relaxed4(cp); c1 = ld_relaxed4(cp + LT);
                    if (!__any_sync(0xffffffffu, ((c0.w ^ tag) | (c1.w ^ tag)) >> 27) || it >= SPIN_LIMIT) break;
                }
                if (tl == 0) PROF(26);
                if ((c0.w | c1.w) & W_OVF)  sts32(bars + MI_SLOW, 1);
                if ((c0.w | c1.w) & W_EBAD) sts32(bars + MI_EBAD, 1);
                uint32_t w[10] = {__byte_perm(c0.x, c0.z, 0x6610), __byte_perm(c0.x, c0.z, 0x7732), __byte_perm(c0.y, c0.w, 0x4410), __byte_perm(c0.y, c0.w, 0x5532), __byte_perm(c0.z, c0.w, 0x6610),
                                  __byte_perm(c1.x, c1.z, 0x6610), __byte_perm(c1.x, c1.z, 0x7732), __byte_perm(c1.y, c1.w, 0x4410), __byte_perm(c1.y, c1.w, 0x5532), __byte_perm(c1.z, c1.w, 0x6610)};
                {
                    uint32_t c[10];
#pragma unroll
                    for (int m = 0; m < 10; ++m) {
                        const uint32_t a = (w[m] >> 12) & 0xffcu;
                        c[m] = atoms_add(sb + X_CNT + a, a < NPC * 32);
                        w[m] = (w[m] & 0x3fffu) + (a << 15);
                    }
#pragma unroll
                    for (int m = 0; m < 10; ++m) w[m] += (c[m] > 7 ? 0x20000u : c[m]) << 14;
                }
                bar_sync(2, LT);
                if (tl == 0) { mbar_arrive(bars + B_LF); PROF(27); }
                if (lw < 3) {
                    const int d0 = min(tl, NPC - 8 + (tl & 7));
                    const int dl = d0 ^ ((d0 >> 3) & 1);
                    const uint4 n0 = lds128(sb + X_CNT + dl * 32), n1 = lds128(sb + X_CNT + dl * 32 + 16);
                    uint32_t pk = min(n0.x, 8u) + (min(n0.y, 8u) << 4) + (min(n0.z, 8u) << 8) + (min(n0.w, 8u) << 12) +
                                  (min(n1.x, 8u) << 16) + (min(n1.y, 8u) << 20) + (min(n1.z, 8u) << 24) + (min(n1.w, 8u) << 28);
                    pk = __funnelshift_r(pk, pk, 4 * lane);
                    uint32_t du = 0xf0000000u, ru = 0, b[8] = {0, 0, 0, 0, 0, 0, 0, 0};
                    auto code2 = [&](uint32_t b0, uint32_t b1) {
                        return __byte_perm(__float_as_uint(__uint_as_float(b0) * 8388608.f), __float_as_uint(__uint_as_float(b1) * 8388608.f), 0x7632);
                    };
                    uint32_t ta = (lane + 7) * 8;
                    auto pass_on = [&]() {
                        ru = __shfl_sync(0xffffffffu, ru, lane + 1, 8);
                        const uint32_t t0 = (code2(b[0], b[2]) >> 7) + code2(b[1], b[3]) * 2, t1 = (code2(b[4], b[6]) >> 7) + code2(b[5], b[7]) * 2;
                        asm volatile("st.shared.v2.u32 [%0], {%1, %2};" :: "r"(sb + X_TAB + ((dl * 64) | (ta & 56))), "r"(t0), "r"(t1) : "memory");
                        ta += 8;
                    };
                    auto take = [&](uint32_t& m, uint32_t& bit, uint32_t n, int c) {
                        asm("{\n.reg .pred p;\n.reg .b32 u;\nsetp.gt.u32 p, %2, %3;\nadd.u32 u, %0, -1;\nlop3.b32 %1, %0, u, 0, 0x30;\n@p and.b32 %0, %0, u;\n}"
                            : "+r"(m), "=r"(bit) : "r"(n), "r"(c));
                    };
#pragma unroll 1
                    for (int k = 0; k < 8; ++k) {
                        const uint32_t n = pk & 15u;
                        const bool big = __any_sync(0xffffffffu, n > 6);
                        pk >>= 4;
                        pass_on();
                        const uint32_t fr = ~(du | ru);
                        uint32_t m = fr;
#pragma unroll
                        for (int c = 0; c < 6; ++c) take(m, b[c], n, c);
                        if (big) { take(m, b[6], n, 6); take(m, b[7], n, 7); }
                        du |= m ^ fr;
                        ru |= m ^ fr;
                    }
                    pass_on();
                    sts32(sb + X_RU + d0 * 4, ru);
                }
                if (tl == 0) PROF(49);
                mbar_wait(bars + B_MI, 0);
                load_rows();
                bar_sync(2, LT);
                if (tl == 0) PROF(28);
                const int v = LT - 1 - tl;
                if (lw >= 6 && v < 40) {
                    const uint4 b = lds128(sb + X_RU + (v >> 2) * 32), e = lds128(sb + X_RU + (v >> 2) * 32 + 16);
                    const uint32_t f2 = b.x & b.y & b.z & b.w;
                    const uint32_t s0 = (f2 & e.x) | (~f2 & b.x), s1 = (f2 & e.y) | (~f2 & b.y), s2 = (f2 & e.z) | (~f2 & b.z);
                    const uint32_t f1 = s0 & s1, f0 = (f1 & s2) | (~f1 & s0);
                    uint32_t u[4];
#pragma unroll
                    for (int k = 0; k < 4; ++k) {
                        const int sh = (v & 3) * 8 + 2 * k;
                        u[k] = ((((f0 >> sh) & 3u) * 0x8001u) & 0x10001u) + ((((f1 >> sh) & 3u) * 0x10002u) & 0x20002u) + ((((f2 >> sh) & 3u) * 0x20004u) & 0x40004u);
                    }
                    sts128(sb + X_DEF + v * 16, make_uint4(u[0], u[1], u[2], u[3]));
                }
                {
                    uint32_t rd[10];
#pragma unroll
                    for (int m = 0; m < 10; ++m) asm volatile("ld.shared.u8 %0, [%1];" : "=r"(rd[m]) : "r"(sb + X_TAB + min(w[m] >> 14, NPC * 64u)) : "memory");
#pragma unroll
                    for (int m = 0; m < 10; ++m) {
                        rd[m] -= 1;
                        if (rd[m] < 48) sts16(sb + X_IMG + ((w[m] >> 14) & ~63u) + min(rd[m], 31u) * 2, w[m] & 0x3fffu);
                        w[m] |= rd[m] & 0x80000000u;
                    }
                    if (__any_sync(0xffffffffu, (int)(w[0] | w[1] | w[2] | w[3] | w[4] | w[5] | w[6] | w[7] | w[8] | w[9]) < 0)) {
                        uint32_t n = 0;
#pragma unroll
                        for (int m = 0; m < 10; ++m) n += w[m] >> 31;
                        uint32_t o = atoms_add(bars + MI_NOVF, n);
#pragma unroll
                        for (int m = 0; m < 10; ++m) {
                            if ((int)w[m] < 0) sts32(bars + MI_OVF + min(o, (uint32_t)OVCAP - 1) * 4, ((w[m] >> 6) & 0x1fc000u) + (w[m] & 0x3fffu) + (node0 * 16384 - 8));
                            o += w[m] >> 31;
                        }
                    }
                }
                bar_sync(2, LT);
                if (tl == 0) PROF(29);
#pragma unroll 1
                for (int set = lw; set < 10; set += lw >= 3 && lw < 5 ? 5 : 10) publish(set);
            }
            warp_arrive(bars + B_XF);
            if (tl == 0) PROF(30);
            if (rowcta) attend();
        }
        Unit x0, x1;
        const uint4* ip = p.idx + quarter * (UPQ * 64) + lane;
        auto fetch = [&](Unit& x, int j) { x.a = ld_relaxed4(ip + j * 64); x.b = ld_relaxed4(ip + j * 64 + 32); };
        mbar_wait(bars + B_GO, 0);
        fetch(x0, wi);
        const uint32_t stg = sb + SM_X + (lane & 15) * 16;
        const uint32_t lt = list_tag(lds32(bars + MI_EPOCH)), base = sS - (lt & 0xffffu) * 16;
        const int nu = UPQ + (quarter == 3);
        int u = wi;
        auto unit = [&](Unit& c, Unit& n) {
#pragma unroll 1
            for (int it = 0;; ++it) {
                if (!__any_sync(0xffffffffu, unit_stale(c, lt) > (it < SPIN_LIMIT ? 0u : 0xffffu))) break;
                fetch(c, u);
            }
            if (u >= 4 * AW) { mbar_wait(bars + B_TF, 0); __syncwarp(); }
            if (u + AW < nu) fetch(n, u + AW);
            agg_unit(c, base, stg + u * 256, lt);
            warp_arrive(bars + B_RND + min((u * 171) >> 11, 12) * 8);
            u += AW;
        };
        mbar_wait(bars + B_S, 0);
        if (rowcta) mbar_wait(bars + B_VE, 0);
        __syncwarp();
        if (tid == 0) PROF(20);
        if (tid == GT) PROF(4);
#pragma unroll 1
        for (;;) {
            unit(x0, x1);
            if (u >= nu) break;
            unit(x1, x0);
            if (u >= nu) break;
        }
        if (tid == 0) PROF(21);
        if (rowcta && slow_cta()) { mbar_wait(bars + B_RV, 0); local_generic(p, node0, wi, lane); }
    }
    PROF_FLUSH();
}

typedef CUresult (*EncodeFn)(CUtensorMap*, CUtensorMapDataType, cuuint32_t, void*, const cuuint64_t*, const cuuint64_t*,
                             const cuuint32_t*, const cuuint32_t*, CUtensorMapInterleave, CUtensorMapSwizzle,
                             CUtensorMapL2promotion, CUtensorMapFloatOOBfill);

static void make_map(EncodeFn enc, CUtensorMap* m, const void* ptr, int rows, int box_cols, int box_rows) {
    cuuint64_t dims[2] = {(cuuint64_t)D, (cuuint64_t)rows};
    cuuint64_t strides[1] = {(cuuint64_t)D * 2};
    cuuint32_t box[2] = {(cuuint32_t)box_cols, (cuuint32_t)box_rows};
    cuuint32_t es[2] = {1u, 1u};
    enc(m, CU_TENSOR_MAP_DATA_TYPE_BFLOAT16, 2, const_cast<void*>(ptr), dims, strides, box, es, CU_TENSOR_MAP_INTERLEAVE_NONE,
        box_cols == 64 ? CU_TENSOR_MAP_SWIZZLE_128B : CU_TENSOR_MAP_SWIZZLE_NONE,
        box_cols == 64 ? CU_TENSOR_MAP_L2_PROMOTION_L2_128B : CU_TENSOR_MAP_L2_PROMOTION_NONE, CU_TENSOR_MAP_FLOAT_OOB_FILL_NONE);
}
static void make_map3(EncodeFn enc, CUtensorMap* m, const void* ptr, int rows, int box_rows) {
    cuuint64_t dims[3] = {64, (cuuint64_t)rows, 4};
    cuuint64_t strides[2] = {(cuuint64_t)D * 2, 128};
    cuuint32_t box[3] = {64u, (cuuint32_t)box_rows, 4u};
    cuuint32_t es[3] = {1u, 1u, 1u};
    enc(m, CU_TENSOR_MAP_DATA_TYPE_BFLOAT16, 3, const_cast<void*>(ptr), dims, strides, box, es, CU_TENSOR_MAP_INTERLEAVE_NONE,
        CU_TENSOR_MAP_SWIZZLE_128B, CU_TENSOR_MAP_L2_PROMOTION_L2_256B, CU_TENSOR_MAP_FLOAT_OOB_FILL_NONE);
}

}

extern "C" void kernel_launch(void* const* d_in, const int* in_sizes, int n_in, void* d_out, int out_size) {
    using namespace gk;
    (void)n_in; (void)out_size;
    static EncodeFn enc = nullptr;
    static void *m_ptr, *cells_ptr, *sync_ptr, *h_ptr, *idx_ptr;
    if (!enc) {
        void* fn = nullptr;
        cudaDriverEntryPointQueryResult qr;
        cudaGetDriverEntryPoint("cuTensorMapEncodeTiled", &fn, cudaEnableDefault, &qr);
        enc = (EncodeFn)fn;
        cudaGetSymbolAddress(&m_ptr, g_M);
        cudaGetSymbolAddress(&cells_ptr, g_cells);
        cudaGetSymbolAddress(&sync_ptr, g_sync);
        cudaGetSymbolAddress(&h_ptr, g_H);
        cudaGetSymbolAddress(&idx_ptr, g_idx);
        cudaFuncSetAttribute(fused_kernel, cudaFuncAttributeMaxDynamicSharedMemorySize, SM_ALLOC);
    }
    if (in_sizes[5] != N || in_sizes[0] != N * D) return;
    Params p;
    p.src  = (const int*)d_in[1];
    p.dst  = (const int*)d_in[2];
    p.esrc = (const int*)d_in[3];
    p.edst = (const int*)d_in[4];
    p.sync = (uint32_t*)sync_ptr;
    p.x    = (const char*)d_in[0];
    p.dis  = (const __nv_bfloat16*)d_in[5];
    p.wv   = (const char*)d_in[9];
    p.cells = (uint4*)cells_ptr;
    p.H    = (uint4*)h_ptr;
    p.idx  = (uint4*)idx_ptr;
    p.M    = (uint2*)m_ptr;
    p.out  = (uint4*)d_out;
    p.E  = in_sizes[1];
    p.Ee = in_sizes[3];
    const int chunk = (((p.E + NCTA - 1) / NCTA) + 1) & ~1;
    const bool force_slow = chunk > 5 * LT || (p.E & 1) || p.E < 2;
    p.chunk = force_slow ? 0 : chunk;
    p.edst4 = p.Ee == 4 * N ? p.edst : nullptr;
    if (p.E < 2) p.src = p.dst = (const int*)d_in[0];
    p.Efast = force_slow ? 0 : p.E;

    CUtensorMap tmX, tmWl, tmM, tmWv, tmR, tmO, tmG, tmQ, tmK, tmV3;
    make_map(enc, &tmX, d_in[0], N, 64, NPC);
    make_map3(enc, &tmWl, d_in[6], D, 64);
    make_map3(enc, &tmM, m_ptr, D, 64);
    make_map3(enc, &tmWv, d_in[9], D, 64);
    make_map(enc, &tmR, d_out, N, 64, 16);
    make_map(enc, &tmO, d_out, N, 8, 192);
    make_map(enc, &tmG, d_in[0], N, 256, 1);
    make_map3(enc, &tmQ, d_in[7], D, 16);
    make_map3(enc, &tmK, d_in[8], D, 32);
    make_map3(enc, &tmV3, d_in[9], D, 16);
    fused_kernel<<<NCTA, NTHR, SM_ALLOC, cudaStreamPerThread>>>(p, tmX, tmWl, tmM, tmWv, tmR, tmO, tmG, tmQ, tmK, tmV3);
}
```
